```python
import torch

def _softmax(x, axis=-1):
    return torch.softmax(x, dim=axis)
def _gelu(x):
    return torch.nn.functional.gelu(x, approximate="tanh")
def _silu(x):
    return torch.nn.functional.silu(x)
def _sigmoid(x):
    return torch.sigmoid(x)
def _layernorm(x, axis=-1, eps=1e-5):
    m = x.mean(dim=axis, keepdim=True)
    v = x.var(dim=axis, keepdim=True, unbiased=False)
    return (x - m) / torch.sqrt(v + eps)
def _scatter_add(tgt, idx, src, axis=0):
    return tgt.clone().index_add_(axis, idx, src)
def _segment_sum(src, seg, n):
    out = torch.zeros((n,) + src.shape[1:], dtype=src.dtype)
    return out.index_add_(0, seg, src)
def _pad(x, pw):
    flat = tuple(v for pair in reversed(pw) for v in pair)
    return torch.nn.functional.pad(x, flat)

kernel_name = 'standalone__standard_2d_1d_3d_conv__vision'

def setup_inputs():

    _w = (lambda a: (lambda t: t.to(torch.bfloat16) if t.is_floating_point() else t)(torch.as_tensor(a)))
    H = W = 384
    C = 384
    K = 1
    return {
        "x": _w((lambda *s: torch.randn(*s, dtype=torch.bfloat16) * 0.05)(1, H, W, C)),
        "w": _w((lambda *s: torch.randn(*s, dtype=torch.bfloat16) * 0.05)(K, K, C, C)),
        "b": _w((lambda *s: torch.randn(*s, dtype=torch.bfloat16) * 0.05)(C)),
    }

def reference(x, w, b):
    B, H, W, Cin = x.shape
    K = w.shape[0]
    pl = (K - 1) // 2
    pr = K // 2
    xp = _pad(x, ((0, 0), (pl, pr), (pl, pr), (0, 0)))
    out = sum(
        torch.einsum('bhwc,cd->bhwd', xp[:, i:i+H, j:j+W, :], w[i, j])
        for i in range(K) for j in range(K)
    )
    return out + b[None, None, None, :]
```

```cpp
#include <cuda_runtime.h>
#include <cuda_bf16.h>
#include <cuda.h>
#include <stdint.h>

#define TUNE(name, value) constexpr int name = value
TUNE(RAMP, 3);
TUNE(KSTART, 30);
TUNE(KRAMP, 4);
TUNE(RA_T0, 1025);
TUNE(RA_SKEW, 300);
TUNE(RA_DT, 430);
TUNE(RA_LEAD, 38);
TUNE(RA_FADE, 13);
TUNE(RA_END, 49);
TUNE(RA_MIN, 9);
TUNE(SHALLOW, 12);
TUNE(DRAIN_T0, 2000);
TUNE(DRAIN_END, 9950);
TUNE(DRAIN_DT, 456);
TUNE(DRAIN_PRE, 4);

namespace {

constexpr int C           = 384;
constexpr int TP          = 32;
constexpr int UNIT        = 2;
constexpr int NSTATIC     = 2;
constexpr int KREG        = 4;
constexpr int HANDOVER    = 18;
constexpr int STAGES      = 4;
constexpr int NBUF        = 10;
constexpr int NLOCAL      = 2;
constexpr int STAGE_BYTES = TP * C * 2;
constexpr int OUT_BYTES   = TP * 192 * 2;
constexpr int SLAB_BYTES  = C * 64 * 2;
constexpr int SMEM_OUT    = STAGES * STAGE_BYTES;
constexpr int SMEM_BAR    = SMEM_OUT + NBUF * OUT_BYTES;
constexpr int SMEM_TOTAL  = SMEM_BAR + 512 + 1024;
constexpr int NTHREADS    = 512;
constexpr int SMEM_W      = SMEM_BAR - 3 * SLAB_BYTES;
constexpr int FREE_STAGES = SMEM_W / STAGE_BYTES;
constexpr int KEEP_MAX    = NBUF - 2;
static_assert(SMEM_W % 1024 == 0 && NLOCAL <= FREE_STAGES && FREE_STAGES < NSTATIC * UNIT && NLOCAL <= UNIT, "layout");
static_assert(STAGES == 4, "the shallow mode of the loader assumes four stages");
static_assert(SMEM_TOTAL <= 232448, "too much shared memory");

__device__ unsigned int g_sched;
__device__ unsigned long long g_dry;

__device__ __forceinline__ uint32_t smem_u32(const void* p) { return (uint32_t)__cvta_generic_to_shared(p); }
__device__ __forceinline__ uint32_t now_ns() {
    uint32_t t;
    asm volatile("mov.u32 %0, %%globaltimer_lo;" : "=r"(t));
    return t;
}
__device__ __forceinline__ unsigned long long now_ns64() {
    unsigned long long t;
    asm volatile("mov.u64 %0, %%globaltimer;" : "=l"(t));
    return t;
}
__device__ __forceinline__ int lds(uint32_t addr) {
    int v;
    asm volatile("ld.volatile.shared.b32 %0, [%1];" : "=r"(v) : "r"(addr) : "memory");
    return v;
}
__device__ __forceinline__ void sts(uint32_t addr, int v) {
    asm volatile("st.volatile.shared.b32 [%0], %1;" ::"r"(addr), "r"(v) : "memory");
}
__device__ __forceinline__ void sts_cluster(uint32_t cluster_addr, int v) {
    asm volatile("st.volatile.shared::cluster.b32 [%0], %1;" ::"r"(cluster_addr), "r"(v) : "memory");
}
__device__ __forceinline__ void mbar_init(uint32_t bar, uint32_t count) {
    asm volatile("mbarrier.init.shared::cta.b64 [%0], %1;" ::"r"(bar), "r"(count) : "memory");
}
__device__ __forceinline__ void mbar_expect_tx(uint32_t bar, uint32_t bytes) {
    asm volatile("mbarrier.arrive.expect_tx.shared::cta.b64 _, [%0], %1;" ::"r"(bar), "r"(bytes) : "memory");
}
__device__ __forceinline__ void mbar_arrive(uint32_t bar) {
    asm volatile("mbarrier.arrive.shared::cta.b64 _, [%0];" ::"r"(bar) : "memory");
}
__device__ __forceinline__ void mbar_arrive_cluster(uint32_t cluster_addr) {
    asm volatile("mbarrier.arrive.shared::cluster.b64 _, [%0];" ::"r"(cluster_addr) : "memory");
}
__device__ __forceinline__ bool mbar_try(uint32_t bar, uint32_t parity) {
    uint32_t ok;
    asm volatile("{\n.reg .pred p;\nmbarrier.try_wait.parity.shared::cta.b64 p, [%1], %2;\nselp.u32 %0, 1, 0, p;\n}"
                 : "=r"(ok) : "r"(bar), "r"(parity) : "memory");
    return ok;
}
__device__ __forceinline__ bool mbar_test(uint32_t bar, uint32_t parity) {
    uint32_t ok;
    asm volatile("{\n.reg .pred p;\nmbarrier.test_wait.parity.shared::cta.b64 p, [%1], %2;\nselp.u32 %0, 1, 0, p;\n}"
                 : "=r"(ok) : "r"(bar), "r"(parity) : "memory");
    return ok;
}
constexpr uint32_t WAIT_LIMIT = 1u << 31;
__device__ __forceinline__ void mbar_wait(uint32_t bar, uint32_t parity) {
    if (mbar_try(bar, parity)) return;
    const uint32_t t0 = (uint32_t)clock();
    while (!mbar_try(bar, parity)) { if ((uint32_t)clock() - t0 > WAIT_LIMIT) break; }
}
__device__ __forceinline__ uint32_t mapa(uint32_t addr, uint32_t rank) {
    uint32_t r;
    asm("mapa.shared::cluster.u32 %0, %1, %2;" : "=r"(r) : "r"(addr), "r"(rank));
    return r;
}
__device__ __forceinline__ void fence_async_smem() { asm volatile("fence.proxy.async.shared::cta;" ::: "memory"); }
__device__ __forceinline__ void post_tile(uint32_t bar, uint32_t slot, uint32_t bytes, int value) {
    asm volatile("mbarrier.arrive.expect_tx.shared::cluster.b64 _, [%0], %1;" ::"r"(bar), "r"(bytes) : "memory");
    asm volatile("st.async.weak.shared::cluster.mbarrier::complete_tx::bytes.b32 [%0], %1, [%2];"
                 ::"r"(slot), "r"(value), "r"(bar) : "memory");
}
__device__ __forceinline__ void tma_load_w(uint32_t dst, const CUtensorMap* tm, int ch, uint32_t bar) {
    asm volatile("cp.async.bulk.tensor.3d.shared::cluster.global.mbarrier::complete_tx::bytes [%0], [%1, {%3, %4, %4}], [%2];"
                 ::"r"(dst), "l"(tm), "r"(bar), "r"(ch), "r"(0) : "memory");
}
__device__ __forceinline__ void tma_load_x(uint32_t dst, const CUtensorMap* tm, int tile, uint32_t bar) {
    asm volatile("cp.async.bulk.tensor.4d.shared::cluster.global.mbarrier::complete_tx::bytes"
                 " [%0], [%1, {%4, %4, %4, %3}], [%2];"
                 ::"r"(dst), "l"(tm), "r"(bar), "r"(tile * (TP / 8)), "r"(0) : "memory");
}
__device__ __forceinline__ void tma_load_x_multicast(uint32_t dst, const CUtensorMap* tm, int tile, uint32_t bar) {
    asm volatile("cp.async.bulk.tensor.4d.shared::cluster.global.mbarrier::complete_tx::bytes.multicast::cluster"
                 " [%0], [%1, {%4, %4, %4, %3}], [%2], %5;"
                 ::"r"(dst), "l"(tm), "r"(bar), "r"(tile * (TP / 8)), "r"(0), "h"((uint16_t)3) : "memory");
}
__device__ __forceinline__ void tma_store_out(const CUtensorMap* tm, uint32_t src, int slab, int tile) {
    asm volatile("cp.async.bulk.tensor.4d.global.shared::cta.bulk_group [%0, {%4, %4, %2, %3}], [%1];"
                 ::"l"(tm), "r"(src), "r"(slab), "r"(tile * (TP / 8)), "r"(0) : "memory");
    asm volatile("cp.async.bulk.commit_group;" ::: "memory");
}
__device__ __forceinline__ void l2_prefetch(const void* p, uint32_t bytes) {
    asm volatile("cp.async.bulk.prefetch.L2.global [%0], %1;" ::"l"(p), "r"(bytes) : "memory");
}

__device__ __forceinline__ void l2_prefetch_tile(const CUtensorMap* tm, int tile) {
    asm volatile("cp.async.bulk.prefetch.tensor.2d.L2.global.tile [%0, {%1, %2}];"
                 ::"l"(tm), "r"(0), "r"(tile * (STAGE_BYTES / 128)) : "memory");
}

__device__ __forceinline__ void wgmma_rs(float (&d)[16], const uint32_t (&a)[4], uint64_t desc, int scale_d) {
    asm volatile(
        "{\n.reg .pred p;\nsetp.ne.b32 p, %21, 0;\n"
        "wgmma.mma_async.sync.aligned.m64n32k16.f32.bf16.bf16 "
        "{%0,%1,%2,%3,%4,%5,%6,%7,%8,%9,%10,%11,%12,%13,%14,%15},"
        "{%16,%17,%18,%19}, %20, p, 1, 1, 0;\n}"
        : "+f"(d[0]), "+f"(d[1]), "+f"(d[2]), "+f"(d[3]), "+f"(d[4]), "+f"(d[5]), "+f"(d[6]), "+f"(d[7]),
          "+f"(d[8]), "+f"(d[9]), "+f"(d[10]), "+f"(d[11]), "+f"(d[12]), "+f"(d[13]), "+f"(d[14]), "+f"(d[15])
        : "r"(a[0]), "r"(a[1]), "r"(a[2]), "r"(a[3]), "l"(desc), "r"(scale_d));
}
__device__ __forceinline__ uint32_t cvt_add_bias(float lo, float hi, uint32_t bias2) {
    uint32_t r;
    asm("{\n.reg .b32 t;\ncvt.rn.bf16x2.f32 t, %2, %1;\nadd.rn.bf16x2 %0, t, %3;\n}" : "=r"(r) : "f"(lo), "f"(hi), "r"(bias2));
    return r;
}

__global__ void __cluster_dims__(2, 1, 1) __launch_bounds__(NTHREADS, 1)
conv1x1_kernel(const __grid_constant__ CUtensorMap tm_x, const __grid_constant__ CUtensorMap tm_w,
               const __grid_constant__ CUtensorMap tm_o, const __grid_constant__ CUtensorMap tm_p,
               const __nv_bfloat16* __restrict__ x, const __nv_bfloat16* __restrict__ w,
               const __nv_bfloat16* __restrict__ bias, int num_units) {
    extern __shared__ uint8_t smem_raw[];
    const uint32_t smem = (smem_u32(smem_raw) + 1023u) & ~1023u;
    const uint32_t bar_full   = smem + SMEM_BAR;
    const uint32_t bar_empty  = bar_full + 8 * STAGES;
    const uint32_t bar_ofull  = bar_empty + 8 * STAGES;
    const uint32_t bar_oempty = bar_ofull + 8 * NBUF;
    const uint32_t bar_w      = bar_oempty + 8 * NBUF;
    const uint32_t bar_wfree  = bar_w + 24;
    const uint32_t bar_wloc   = bar_wfree + 8;
    const uint32_t bar_spare  = bar_wloc + 8;
    const uint32_t progress   = bar_spare + 8;
    const uint32_t total_slot = progress + 4;
    const uint32_t tile_slot  = progress + 8;
    const uint32_t otile_slot = tile_slot + 4 * STAGES;

    const int tid = threadIdx.x;
    const int wg  = tid >> 7;
    uint32_t rank;
    asm("mov.u32 %0, %%cluster_ctarank;" : "=r"(rank));
    const int cluster_id = blockIdx.x >> 1;
    const int nclusters  = gridDim.x >> 1;
    const int ntiles     = num_units * UNIT;

    asm volatile("setmaxnreg.dec.sync.aligned.u32 32;");

    if (tid == 384) {
        asm volatile("prefetch.tensormap [%0];" ::"l"(&tm_w) : "memory");
        asm volatile("prefetch.tensormap [%0];" ::"l"(&tm_x) : "memory");
        if (blockIdx.x < 128) l2_prefetch(w + blockIdx.x * (C * C / 128), C * C * 2 / 128);
        for (int g = 0; g < 3; g++) mbar_init(bar_w + 8 * g, 1);
        for (int s = 0; s < NLOCAL; s++) mbar_init(bar_full + 8 * s, 1);
        asm volatile("fence.mbarrier_init.release.cluster;" ::: "memory");
        fence_async_smem();
        for (int g = 0; g < 3; g++) {
            mbar_expect_tx(bar_w + 8 * g, SLAB_BYTES);
            tma_load_w(smem + SMEM_W + g * SLAB_BYTES, &tm_w, rank * 192 + g * 64, bar_w + 8 * g);
        }
        for (int s = 0; s < NLOCAL; s++) {
            sts(tile_slot + 4 * s, cluster_id * UNIT + s);
            mbar_expect_tx(bar_full + 8 * s, STAGE_BYTES);
            tma_load_x(smem + s * STAGE_BYTES, &tm_x, cluster_id * UNIT + s, bar_full + 8 * s);
        }
    }
    if (tid == 416) {
        for (int s = NLOCAL; s < STAGES; s++) mbar_init(bar_full + 8 * s, 1);
        for (int s = 0; s < STAGES; s++) mbar_init(bar_empty + 8 * s, 24);
        for (int s = 0; s < NBUF; s++) {
            mbar_init(bar_ofull + 8 * s, 12);
            mbar_init(bar_oempty + 8 * s, 1);
        }
        mbar_init(bar_wfree, 24);
        mbar_init(bar_wloc, 12);
        mbar_init(bar_spare, 1);
        sts(progress, 0);
        sts(total_slot, 0);
        asm volatile("fence.mbarrier_init.release.cluster;" ::: "memory");
        fence_async_smem();
        asm volatile("prefetch.tensormap [%0];" ::"l"(&tm_o) : "memory");
    }
    uint32_t t_entry = 0;
    if (tid == 448) {
        t_entry = now_ns();
        asm volatile("prefetch.tensormap [%0];" ::"l"(&tm_p) : "memory");
        l2_prefetch(x + ((size_t)cluster_id * (UNIT * TP) + rank * (TP / 2)) * C, STAGE_BYTES / 2);
    }
    __syncwarp();
    asm volatile("barrier.cluster.arrive.relaxed.aligned;" ::: "memory");

    if (wg == 3) {
        asm volatile("barrier.cluster.wait.aligned;" ::: "memory");
        if (tid == 384 && rank == 0) {
            const uint32_t peer = mapa(smem, 1) - smem;
            const int shallow = max(ntiles - SHALLOW * nclusters, STAGES * nclusters);
            int s = NLOCAL, n = 0;
            uint32_t ph = 1;
            int unit = cluster_id;
            for (int u = 0; unit < num_units; u++) {
                const bool late = unit >= num_units - 3 * nclusters;
                const unsigned long long t_fetch = late ? now_ns64() : 0;
                int next = unit - (NSTATIC - 1) * nclusters;
                if (u >= NSTATIC - 1) next = (int)atomicInc(&g_sched, (unsigned)(num_units - (NSTATIC - 1) * nclusters - 1));
#pragma unroll 1
                for (int h = 0; h < UNIT; h++, n++) {
                    if (n < NLOCAL) continue;
                    const int tile = unit * UNIT + h;
                    if (n == FREE_STAGES) mbar_wait(bar_wfree, 0);
                    mbar_wait(bar_empty + 8 * s, ph);
                    if (tile >= shallow) mbar_wait(bar_empty + 8 * ((s + 1) & 3), s == 3 ? ph ^ 1 : ph);
                    const uint32_t bar = bar_full + 8 * s;
                    tma_load_x_multicast(smem + s * STAGE_BYTES, &tm_x, tile, bar);
                    post_tile(bar, tile_slot + 4 * s, STAGE_BYTES + 4, tile);
                    post_tile(bar + peer, tile_slot + 4 * s + peer, STAGE_BYTES + 4, tile);
                    sts_cluster(progress + peer, tile);
                    if (++s == STAGES) { s = 0; ph ^= 1; }
                    if (late && h == 0) {
                        asm volatile("" : "+r"(next)::"memory");
                        const int succ = next + NSTATIC * nclusters;
                        if (succ >= num_units) {
                            sts(total_slot, n + UNIT);
                            sts_cluster(total_slot + peer, n + UNIT);
                        }
                        if (succ == num_units - 1)
                            asm volatile("st.relaxed.gpu.global.b64 [%0], %1;" ::"l"(&g_dry), "l"(t_fetch) : "memory");
                    }
                }
                asm volatile("" : "+r"(next)::"memory");
                unit = next + NSTATIC * nclusters;
            }
            sts_cluster(progress + peer, 0x7fffffff);
            mbar_wait(bar_empty + 8 * s, ph);
            post_tile(bar_full + 8 * s, tile_slot + 4 * s, 4, -1);
            post_tile(bar_full + 8 * s + peer, tile_slot + 4 * s + peer, 4, -1);
#pragma unroll 1
            for (int e = 1; e < STAGES; e++) {
                if (++s == STAGES) { s = 0; ph ^= 1; }
                mbar_wait(bar_empty + 8 * s, ph);
            }
        } else if (tid == 448 && rank == 1) {
            auto wait_loader = [&](int tile) {
                while (lds(progress) < tile && now_ns() - t_entry < 1000000000u) __nanosleep(64);
            };
            const int slope = (RA_LEAD - RA_MIN) * 16 / (RA_END - RA_FADE);
            int lead = RA_LEAD * 16;
            uint32_t due = RA_T0 + cluster_id * RA_SKEW / nclusters;
#pragma unroll 1
            for (int j = NLOCAL; j * nclusters < ntiles; j++, due += RA_DT) {
                const int t = j < NSTATIC * UNIT ? (cluster_id + (j / UNIT) * nclusters) * UNIT + j % UNIT
                                                 : j * nclusters + cluster_id;
                if (j >= RA_FADE && j < RA_END) lead -= slope;
                wait_loader(t - (lead * nclusters >> 6));
                while (now_ns() - t_entry < due) {}
                if (t < ntiles) l2_prefetch_tile(&tm_p, t);
            }
            wait_loader(0x7fffffff);
        } else if (tid == 416) {
            uint32_t base = smem;
            asm volatile("" : "+r"(base));
            const uint32_t ofull = base + (bar_ofull - smem), otile = base + (otile_slot - smem);
            uint32_t prev = base + (bar_spare - smem);
            int fs = 0, is = 0;
            int filled = 0, issued = 0;
            int keep = 0, step = RAMP + 1 - cluster_id % RAMP;
            uint32_t fph = 0, iph = 0;
            auto store = [&](int tile) {
                tma_store_out(&tm_o, base + SMEM_OUT + is * OUT_BYTES, rank * 3, tile);
                asm volatile("cp.async.bulk.wait_group.read 1;" ::: "memory");
                mbar_arrive(prev);
                prev = ofull + 8 * (NBUF + is);
                issued++;
                if (++is == NBUF) { is = 0; iph ^= 1; }
            };
            auto next_filled = [&]() -> int {
                const int tile = lds(otile + 4 * (filled & 31));
                if (tile >= 0) {
                    if (++fs == NBUF) { fs = 0; fph ^= 1; }
                    if (++filled == step) { step += RAMP; keep = min(keep + 1, KEEP_MAX); }
                    if (filled - issued > keep) store(lds(otile + 4 * (issued & 31)));
                }
                return tile;
            };
            const unsigned long long t_start = now_ns64();
            const int near_end = ntiles - (KREG + NBUF) * nclusters;
            int tile;
            do {
                mbar_wait(ofull + 8 * fs, fph);
                tile = next_filled();
            } while (tile >= 0 && tile < near_end);
            bool armed = false;
            uint32_t t_dry = 0, due = 0;
            for (uint32_t it = 0; it < (1u << 22); it++) {
                if (tile >= 0 && mbar_test(ofull + 8 * fs, fph)) tile = next_filled();
                if (armed) {
                    int total = lds(base + (total_slot - smem));
                    if (total == 0) total = filled + KREG + STAGES + DRAIN_PRE;
                    due = t_dry + max(DRAIN_T0, DRAIN_END - (total - issued) * DRAIN_DT);
                    if ((int)(now_ns() - due) >= 0) break;
                } else {
                    unsigned long long v;
                    asm volatile("ld.relaxed.gpu.global.b64 %0, [%1];" : "=l"(v) : "l"(&g_dry) : "memory");
                    if (v > t_start) { armed = true; t_dry = (uint32_t)v; }
                    else if (tile < 0) break;
                }
            }
            if (!armed) { due = now_ns(); t_dry = due - DRAIN_END; }
            int total;
            while ((total = lds(base + (total_slot - smem))) == 0) {
                mbar_wait(ofull + 8 * is, iph);
                tile = lds(otile + 4 * (issued & 31));
                if (tile < 0) break;
                while ((int)(now_ns() - due) < 0) {}
                due += DRAIN_DT;
                store(tile);
            }
            due = t_dry + DRAIN_END - (total - issued) * DRAIN_DT;
#pragma unroll 1
            while (issued < total) {
                mbar_wait(ofull + 8 * is, iph);
                tile = lds(otile + 4 * (issued & 31));
                while ((int)(now_ns() - due) < 0) {}
                due += DRAIN_DT;
                store(tile);
            }
            asm volatile("cp.async.bulk.wait_group.read 0;" ::: "memory");
        }
    } else {
        asm volatile("setmaxnreg.inc.sync.aligned.u32 160;");
        const int lane = tid & 31;
        const int warp = (tid >> 5) & 3;
        if (wg == 2) asm volatile("bar.arrive 8, 256;" ::: "memory");

        uint32_t bias_lo, bias_hi;
        {
            const unsigned short* bp =
                reinterpret_cast<const unsigned short*>(bias) + rank * 192 + wg * 64 + warp * 16 + (lane >> 2);
            const uint32_t b0 = bp[0], b1 = bp[8];
            bias_lo = b0 | (b0 << 16);
            bias_hi = b1 | (b1 << 16);
        }
        const uint32_t swz = (uint32_t)(((warp * 2 + ((lane >> 3) & 1)) ^ (lane & 7)) << 4);
        const uint32_t lead = mapa(smem, 0) - smem;

        uint32_t a[24][4];
        asm volatile("barrier.cluster.wait.aligned;" ::: "memory");
        mbar_wait(bar_w + 8 * wg, 0);
        {
            const uint32_t base = smem + SMEM_W + wg * SLAB_BYTES + ((lane >> 4) * 8 + (lane & 7)) * 128 + swz;
#pragma unroll
            for (int ks = 0; ks < 24; ks++)
                asm volatile("ldmatrix.sync.aligned.m8n8.x4.trans.shared.b16 {%0,%1,%2,%3}, [%4];"
                             : "=r"(a[ks][0]), "=r"(a[ks][1]), "=r"(a[ks][2]), "=r"(a[ks][3])
                             : "r"(base + ks * 2048) : "memory");
        }
        fence_async_smem();
        __syncwarp();
        if (lane == 0) {
            mbar_arrive_cluster(bar_wfree + lead);
            mbar_arrive(bar_wloc);
        }

        uint32_t st_base = smem + SMEM_OUT + wg * 1024 + (lane >> 4) * 3072 + (lane & 7) * 128 + swz;
        uint32_t my_turn = 8 + wg, next_turn = wg == 2 ? 8 : 9 + wg;
        asm volatile("" : "+r"(st_base), "+r"(my_turn), "+r"(next_turn));
        const uint64_t desc0 = (uint64_t)((smem & 0x3FFFF) >> 4) | (1ull << 16) | ((6144ull >> 4) << 32) | (1ull << 62);

        int s = 0, ob = 0, i = 0;
        uint32_t ph = 0, oph = 1;
        float d[16];
        uint32_t q[KREG][8];
        auto compute = [&]() -> bool {
            mbar_wait(bar_full + 8 * s, ph);
            const int tile = lds(tile_slot + 4 * s);
            if (tid == 0) sts(otile_slot + 4 * (i & 31), tile);
            if (tile < 0) return false;
            const uint64_t desc = desc0 + (uint64_t)(s * (STAGE_BYTES >> 4));
            asm volatile("bar.sync %0, 256;" ::"r"(my_turn) : "memory");
            asm volatile("wgmma.fence.sync.aligned;" ::: "memory");
#pragma unroll
            for (int ks = 0; ks < 24; ks++) {
                wgmma_rs(d, a[ks], desc + (uint64_t)(((ks >> 2) * 1024 + (ks & 3) * 32) >> 4), ks != 0);
                if (ks == HANDOVER - 1) asm volatile("bar.arrive %0, 256;" ::"r"(next_turn) : "memory");
            }
            asm volatile("wgmma.commit_group.sync.aligned;" ::: "memory");
            asm volatile("wgmma.wait_group.sync.aligned 0;" ::: "memory");
#pragma unroll
            for (int j = 0; j < 16; j++) asm volatile("" : "+f"(d[j])::"memory");
            if (lane == 0) mbar_arrive_cluster(bar_empty + 8 * s + lead);
            if (++s == STAGES) { s = 0; ph ^= 1; }
            return true;
        };
        auto pack = [&](uint32_t (&p)[8]) {
#pragma unroll
            for (int j = 0; j < 8; j++) p[j] = cvt_add_bias(d[2 * j], d[2 * j + 1], (j & 1) ? bias_hi : bias_lo);
        };
        auto emit = [&](int head) {
            mbar_wait(bar_oempty + 8 * ob, oph);
            const uint32_t st = st_base + ob * OUT_BYTES;
#pragma unroll
            for (int k = 0; k < KREG; k++)
                if (head == k) {
#pragma unroll
                    for (int j = 0; j < 2; j++)
                        asm volatile("stmatrix.sync.aligned.m8n8.x4.trans.shared.b16 [%0], {%1,%2,%3,%4};"
                                     ::"r"(st + j * 6144), "r"(q[k][4 * j]), "r"(q[k][4 * j + 1]),
                                       "r"(q[k][4 * j + 2]), "r"(q[k][4 * j + 3]) : "memory");
                }
            fence_async_smem();
            __syncwarp();
            if (lane == 0) mbar_arrive(bar_ofull + 8 * ob);
            if (++ob == NBUF) { ob = 0; oph ^= 1; }
        };

        const int kstart = KSTART - cluster_id % KRAMP;
        bool more = true;
#pragma unroll 1
        for (; i < kstart; i++) {
            more = compute();
            if (!more) break;
            pack(q[0]);
            if (i == 0) mbar_wait(bar_wloc, 0);
            emit(0);
        }
        int held = 0, head = 0, tail = 0, target = 1, kstep = kstart + KRAMP;
#pragma unroll 1
        for (; more || held > 0; i++) {
            if (more) more = compute();
            if (i == kstep) { kstep += KRAMP; target = min(target + 1, KREG); }
            if (held > 0 && (!more || held == target)) {
                emit(head);
                held--;
                if (++head == KREG) head = 0;
            }
            if (more) {
#pragma unroll
                for (int k = 0; k < KREG; k++)
                    if (tail == k) pack(q[k]);
                held++;
                if (++tail == KREG) tail = 0;
            }
        }
        mbar_wait(bar_oempty + 8 * ob, oph);
        if (lane == 0) mbar_arrive(bar_ofull + 8 * ob);
        if (wg == 0) asm volatile("bar.sync 8, 256;" ::: "memory");
    }
}

typedef CUresult (*EncodeTiledFn)(CUtensorMap*, CUtensorMapDataType, cuuint32_t, void*, const cuuint64_t*,
                                  const cuuint64_t*, const cuuint32_t*, const cuuint32_t*, CUtensorMapInterleave,
                                  CUtensorMapSwizzle, CUtensorMapL2promotion, CUtensorMapFloatOOBfill);

void encode_map(EncodeTiledFn fn, CUtensorMap* tm, const void* ptr, int rank, const cuuint64_t* dims,
                const cuuint64_t* strides, const cuuint32_t* box) {
    const cuuint32_t estr[4] = {1, 1, 1, 1};
    fn(tm, CU_TENSOR_MAP_DATA_TYPE_BFLOAT16, rank, const_cast<void*>(ptr), dims, strides, box, estr,
       CU_TENSOR_MAP_INTERLEAVE_NONE, CU_TENSOR_MAP_SWIZZLE_128B, CU_TENSOR_MAP_L2_PROMOTION_L2_128B,
       CU_TENSOR_MAP_FLOAT_OOB_FILL_NONE);
}

}

extern "C" void kernel_launch(void* const* d_in, const int* in_sizes, int n_in, void* d_out, int out_size) {
    const __nv_bfloat16* x = (const __nv_bfloat16*)d_in[0];
    const __nv_bfloat16* w = (const __nv_bfloat16*)d_in[1];
    const __nv_bfloat16* b = (const __nv_bfloat16*)d_in[2];
    const int pixels = in_sizes[0] / C;

    static EncodeTiledFn encode = nullptr;
    static int max_clusters = 0;
    if (!encode) {
        void* fn = nullptr;
        cudaDriverEntryPointQueryResult qr;
        cudaGetDriverEntryPoint("cuTensorMapEncodeTiled", &fn, cudaEnableDefault, &qr);
        encode = (EncodeTiledFn)fn;
        cudaFuncSetAttribute(conv1x1_kernel, cudaFuncAttributeMaxDynamicSharedMemorySize, SMEM_TOTAL);
        cudaLaunchConfig_t cfg = {};
        cfg.gridDim = dim3(2, 1, 1);
        cfg.blockDim = dim3(NTHREADS, 1, 1);
        cfg.dynamicSmemBytes = SMEM_TOTAL;
        cudaLaunchAttribute at[1];
        at[0].id = cudaLaunchAttributeClusterDimension;
        at[0].val.clusterDim.x = 2; at[0].val.clusterDim.y = 1; at[0].val.clusterDim.z = 1;
        cfg.attrs = at; cfg.numAttrs = 1;
        if (cudaOccupancyMaxActiveClusters(&max_clusters, conv1x1_kernel, &cfg) != cudaSuccess || max_clusters <= 0) {
            (void)cudaGetLastError();
            int dev = 0, sms = 0;
            cudaGetDevice(&dev);
            cudaDeviceGetAttribute(&sms, cudaDevAttrMultiProcessorCount, dev);
            max_clusters = sms / 2;
        }
    }
    CUtensorMap tm_x, tm_w, tm_o, tm_p;
    {
        const cuuint64_t dims[4]    = {64, 8, 6, (cuuint64_t)(pixels / 8)};
        const cuuint64_t strides[3] = {C * 2, 128, C * 2 * 8};
        const cuuint32_t box_x[4]   = {64, 8, 6, TP / 8};
        const cuuint32_t box_o[4]   = {64, 8, 3, TP / 8};
        encode_map(encode, &tm_x, x, 4, dims, strides, box_x);
        encode_map(encode, &tm_o, d_out, 4, dims, strides, box_o);
        const cuuint64_t pdims[2]    = {64, (cuuint64_t)pixels * 6};
        const cuuint64_t pstrides[1] = {128};
        const cuuint32_t pbox[2]     = {64, STAGE_BYTES / 128};
        encode_map(encode, &tm_p, x, 2, pdims, pstrides, pbox);
        const cuuint64_t wdims[3]    = {C, 192, 2};
        const cuuint64_t wstrides[2] = {C * 2, C * 2 * 192};
        const cuuint32_t wbox[3]     = {64, 192, 2};
        encode_map(encode, &tm_w, w, 3, wdims, wstrides, wbox);
    }
    const int num_units = pixels / (TP * UNIT);
    const int nclusters = max_clusters * NSTATIC <= num_units ? max_clusters : num_units / NSTATIC;
    conv1x1_kernel<<<2 * nclusters, NTHREADS, SMEM_TOTAL, cudaStreamPerThread>>>(tm_x, tm_w, tm_o, tm_p, x, w, b, num_units);
}
```

```cpp
#include <cuda_runtime.h>
#include <cuda_bf16.h>
#include <cuda.h>
#include <stdint.h>

#define TUNE(name, value) constexpr int name = value
TUNE(RAMP_Q, 10);
TUNE(KSTART, 27);
TUNE(KRAMP, 3);
TUNE(X1_T, 250);
TUNE(RA_T0, 1150);
TUNE(RA_SKEW, 150);
TUNE(RA_DT, 468);
TUNE(RA_LEAD, 38);
TUNE(RA_FADE, 13);
TUNE(RA_END, 53);
TUNE(RA_MIN, 11);
TUNE(SHALLOW, 13);
TUNE(DRAIN_T0, 1100);
TUNE(DRAIN_END, 10740);
TUNE(DRAIN_DT, 453);
TUNE(DRAIN_PRE, 5);

namespace {

constexpr int C           = 384;
constexpr int TP          = 32;
constexpr int UNIT        = 2;
constexpr int NSTATIC     = 2;
constexpr int KREG        = 5;
constexpr int HANDOVER    = 18;
constexpr int STAGES      = 4;
constexpr int NBUF        = 10;
constexpr int NLOCAL      = 2;
constexpr int STAGE_BYTES = TP * C * 2;
constexpr int OUT_BYTES   = TP * 192 * 2;
constexpr int SLAB_BYTES  = C * 64 * 2;
constexpr int SMEM_OUT    = STAGES * STAGE_BYTES;
constexpr int SMEM_BAR    = SMEM_OUT + NBUF * OUT_BYTES;
constexpr int SMEM_TOTAL  = SMEM_BAR + 512 + 1024;
constexpr int NTHREADS    = 512;
constexpr int SMEM_W      = SMEM_BAR - 3 * SLAB_BYTES;
constexpr int FREE_STAGES = SMEM_W / STAGE_BYTES;
static_assert(SMEM_W % 1024 == 0 && NLOCAL <= FREE_STAGES && FREE_STAGES < NSTATIC * UNIT && NLOCAL <= UNIT, "layout");
static_assert(STAGES == 4, "the shallow mode of the loader assumes four stages");
static_assert(SMEM_TOTAL <= 232448, "too much shared memory");

__device__ unsigned int g_sched;
__device__ unsigned long long g_dry;

__device__ __forceinline__ uint32_t smem_u32(const void* p) { return (uint32_t)__cvta_generic_to_shared(p); }
__device__ __forceinline__ uint32_t now_ns() {
    uint32_t t;
    asm volatile("mov.u32 %0, %%globaltimer_lo;" : "=r"(t));
    return t;
}
__device__ __forceinline__ unsigned long long now_ns64() {
    unsigned long long t;
    asm volatile("mov.u64 %0, %%globaltimer;" : "=l"(t));
    return t;
}
__device__ __forceinline__ int lds(uint32_t addr) {
    int v;
    asm volatile("ld.volatile.shared.b32 %0, [%1];" : "=r"(v) : "r"(addr) : "memory");
    return v;
}
__device__ __forceinline__ void sts(uint32_t addr, int v) {
    asm volatile("st.volatile.shared.b32 [%0], %1;" ::"r"(addr), "r"(v) : "memory");
}
__device__ __forceinline__ void sts_cluster(uint32_t cluster_addr, int v) {
    asm volatile("st.volatile.shared::cluster.b32 [%0], %1;" ::"r"(cluster_addr), "r"(v) : "memory");
}
__device__ __forceinline__ void mbar_init(uint32_t bar, uint32_t count) {
    asm volatile("mbarrier.init.shared::cta.b64 [%0], %1;" ::"r"(bar), "r"(count) : "memory");
}
__device__ __forceinline__ void mbar_expect_tx(uint32_t bar, uint32_t bytes) {
    asm volatile("mbarrier.arrive.expect_tx.shared::cta.b64 _, [%0], %1;" ::"r"(bar), "r"(bytes) : "memory");
}
__device__ __forceinline__ void mbar_arrive(uint32_t bar) {
    asm volatile("mbarrier.arrive.shared::cta.b64 _, [%0];" ::"r"(bar) : "memory");
}
__device__ __forceinline__ void mbar_arrive_cluster(uint32_t cluster_addr) {
    asm volatile("mbarrier.arrive.shared::cluster.b64 _, [%0];" ::"r"(cluster_addr) : "memory");
}
__device__ __forceinline__ bool mbar_try(uint32_t bar, uint32_t parity) {
    uint32_t ok;
    asm volatile("{\n.reg .pred p;\nmbarrier.try_wait.parity.shared::cta.b64 p, [%1], %2;\nselp.u32 %0, 1, 0, p;\n}"
                 : "=r"(ok) : "r"(bar), "r"(parity) : "memory");
    return ok;
}
__device__ __forceinline__ bool mbar_test(uint32_t bar, uint32_t parity) {
    uint32_t ok;
    asm volatile("{\n.reg .pred p;\nmbarrier.test_wait.parity.shared::cta.b64 p, [%1], %2;\nselp.u32 %0, 1, 0, p;\n}"
                 : "=r"(ok) : "r"(bar), "r"(parity) : "memory");
    return ok;
}
__device__ __forceinline__ void mbar_wait(uint32_t bar, uint32_t parity) {
    asm volatile("{\n.reg .pred p, q;\n.reg .u32 n;\n"
                 "mbarrier.try_wait.parity.shared::cta.b64 p, [%0], %1;\n@p bra DONE;\nmov.u32 n, 0;\n"
                 "AGAIN:\nmbarrier.try_wait.parity.shared::cta.b64 p, [%0], %1;\nadd.u32 n, n, 1;\n"
                 "setp.lt.and.u32 q, n, 0x400000, !p;\n@q bra AGAIN;\nDONE:\n}"
                 ::"r"(bar), "r"(parity) : "memory");
}
__device__ __forceinline__ uint32_t mapa(uint32_t addr, uint32_t rank) {
    uint32_t r;
    asm("mapa.shared::cluster.u32 %0, %1, %2;" : "=r"(r) : "r"(addr), "r"(rank));
    return r;
}
__device__ __forceinline__ void fence_async_smem() { asm volatile("fence.proxy.async.shared::cta;" ::: "memory"); }
__device__ __forceinline__ void post_tile(uint32_t bar, uint32_t slot, uint32_t bytes, int value) {
    asm volatile("mbarrier.arrive.expect_tx.shared::cluster.b64 _, [%0], %1;" ::"r"(bar), "r"(bytes) : "memory");
    asm volatile("st.async.weak.shared::cluster.mbarrier::complete_tx::bytes.b32 [%0], %1, [%2];"
                 ::"r"(slot), "r"(value), "r"(bar) : "memory");
}
__device__ __forceinline__ void tma_load_w(uint32_t dst, const CUtensorMap* tm, int ch, uint32_t bar) {
    asm volatile("cp.async.bulk.tensor.3d.shared::cluster.global.mbarrier::complete_tx::bytes [%0], [%1, {%3, %4, %4}], [%2];"
                 ::"r"(dst), "l"(tm), "r"(bar), "r"(ch), "r"(0) : "memory");
}
__device__ __forceinline__ void tma_load_x(uint32_t dst, const CUtensorMap* tm, int tile, uint32_t bar) {
    asm volatile("cp.async.bulk.tensor.4d.shared::cluster.global.mbarrier::complete_tx::bytes"
                 " [%0], [%1, {%4, %4, %4, %3}], [%2];"
                 ::"r"(dst), "l"(tm), "r"(bar), "r"(tile * (TP / 8)), "r"(0) : "memory");
}
__device__ __forceinline__ void tma_load_x_multicast(uint32_t dst, const CUtensorMap* tm, int tile, uint32_t bar) {
    asm volatile("cp.async.bulk.tensor.4d.shared::cluster.global.mbarrier::complete_tx::bytes.multicast::cluster"
                 " [%0], [%1, {%4, %4, %4, %3}], [%2], %5;"
                 ::"r"(dst), "l"(tm), "r"(bar), "r"(tile * (TP / 8)), "r"(0), "h"((uint16_t)3) : "memory");
}
__device__ __forceinline__ void tma_store_out(const CUtensorMap* tm, uint32_t src, int slab, int tile) {
    asm volatile("cp.async.bulk.tensor.4d.global.shared::cta.bulk_group [%0, {%4, %4, %2, %3}], [%1];"
                 ::"l"(tm), "r"(src), "r"(slab), "r"(tile * (TP / 8)), "r"(0) : "memory");
    asm volatile("cp.async.bulk.commit_group;" ::: "memory");
}
__device__ __forceinline__ void l2_prefetch(const void* p, uint32_t bytes) {
    asm volatile("cp.async.bulk.prefetch.L2.global [%0], %1;" ::"l"(p), "r"(bytes) : "memory");
}

__device__ __forceinline__ void l2_prefetch_tile(const CUtensorMap* tm, int tile) {
    asm volatile("cp.async.bulk.prefetch.tensor.2d.L2.global.tile [%0, {%1, %2}];"
                 ::"l"(tm), "r"(0), "r"(tile * (STAGE_BYTES / 128)) : "memory");
}

__device__ __forceinline__ void wgmma_rs(float (&d)[16], const uint32_t (&a)[4], uint64_t desc, int scale_d) {
    asm volatile(
        "{\n.reg .pred p;\nsetp.ne.b32 p, %21, 0;\n"
        "wgmma.mma_async.sync.aligned.m64n32k16.f32.bf16.bf16 "
        "{%0,%1,%2,%3,%4,%5,%6,%7,%8,%9,%10,%11,%12,%13,%14,%15},"
        "{%16,%17,%18,%19}, %20, p, 1, 1, 0;\n}"
        : "+f"(d[0]), "+f"(d[1]), "+f"(d[2]), "+f"(d[3]), "+f"(d[4]), "+f"(d[5]), "+f"(d[6]), "+f"(d[7]),
          "+f"(d[8]), "+f"(d[9]), "+f"(d[10]), "+f"(d[11]), "+f"(d[12]), "+f"(d[13]), "+f"(d[14]), "+f"(d[15])
        : "r"(a[0]), "r"(a[1]), "r"(a[2]), "r"(a[3]), "l"(desc), "r"(scale_d));
}
template <bool HI>
__device__ __forceinline__ uint32_t cvt_add_bias(float lo, float hi, uint32_t bias2) {
    uint32_t r;
    if (HI) asm("{\n.reg .b32 t, b;\n.reg .b16 l, h;\ncvt.rn.bf16x2.f32 t, %2, %1;\nmov.b32 {l, h}, %3;\nmov.b32 b, {h, h};\n"
                "add.rn.bf16x2 %0, t, b;\n}" : "=r"(r) : "f"(lo), "f"(hi), "r"(bias2));
    else asm("{\n.reg .b32 t, b;\n.reg .b16 l, h;\ncvt.rn.bf16x2.f32 t, %2, %1;\nmov.b32 {l, h}, %3;\nmov.b32 b, {l, l};\n"
             "add.rn.bf16x2 %0, t, b;\n}" : "=r"(r) : "f"(lo), "f"(hi), "r"(bias2));
    return r;
}

__global__ void __cluster_dims__(2, 1, 1) __launch_bounds__(NTHREADS, 1)
conv1x1_kernel(const __grid_constant__ CUtensorMap tm_x, const __grid_constant__ CUtensorMap tm_w,
               const __grid_constant__ CUtensorMap tm_o, const __grid_constant__ CUtensorMap tm_p,
               const __nv_bfloat16* __restrict__ x, const __nv_bfloat16* __restrict__ w,
               const __nv_bfloat16* __restrict__ bias, int num_units) {
    extern __shared__ uint8_t smem_raw[];
    const uint32_t smem = (smem_u32(smem_raw) + 1023u) & ~1023u;
    const uint32_t bar_full   = smem + SMEM_BAR;
    const uint32_t bar_empty  = bar_full + 8 * STAGES;
    const uint32_t bar_ofull  = bar_empty + 8 * STAGES;
    const uint32_t bar_oempty = bar_ofull + 8 * NBUF;
    const uint32_t bar_w      = bar_oempty + 8 * NBUF;
    const uint32_t bar_wfree  = bar_w + 24;
    const uint32_t bar_wloc   = bar_wfree + 8;
    const uint32_t bar_spare  = bar_wloc + 8;
    const uint32_t progress   = bar_spare + 16;
    const uint32_t total_slot = progress + 4;
    const uint32_t dry_slot   = progress + 8;
    const uint32_t tile_slot  = progress + 16;

    const int tid = threadIdx.x;
    const int wg  = tid >> 7;
    uint32_t rank;
    asm("mov.u32 %0, %%cluster_ctarank;" : "=r"(rank));
    const int cluster_id = blockIdx.x >> 1;
    const int nclusters  = gridDim.x >> 1;
    const int ntiles     = num_units * UNIT;

    asm volatile("setmaxnreg.dec.sync.aligned.u32 32;");

    if (tid == 384) {
        asm volatile("prefetch.tensormap [%0];" ::"l"(&tm_w) : "memory");
        asm volatile("prefetch.tensormap [%0];" ::"l"(&tm_x) : "memory");
        if (blockIdx.x < 128) l2_prefetch(w + blockIdx.x * (C * C / 128), C * C * 2 / 128);
        for (int g = 0; g < 3; g++) mbar_init(bar_w + 8 * g, 1);
        for (int s = 0; s < NLOCAL; s++) mbar_init(bar_full + 8 * s, 1);
        asm volatile("fence.mbarrier_init.release.cluster;" ::: "memory");
        fence_async_smem();
        for (int g = 0; g < 3; g++) {
            mbar_expect_tx(bar_w + 8 * g, SLAB_BYTES);
            tma_load_w(smem + SMEM_W + g * SLAB_BYTES, &tm_w, rank * 192 + g * 64, bar_w + 8 * g);
        }
        for (int s = 0; s < NLOCAL; s++) {
            sts(tile_slot + 4 * s, cluster_id * UNIT + s);
            mbar_expect_tx(bar_full + 8 * s, STAGE_BYTES);
            tma_load_x(smem + s * STAGE_BYTES, &tm_x, cluster_id * UNIT + s, bar_full + 8 * s);
        }
    }
    if (tid == 416) {
        for (int s = NLOCAL; s < STAGES; s++) mbar_init(bar_full + 8 * s, 1);
        for (int s = 0; s < STAGES; s++) mbar_init(bar_empty + 8 * s, 24);
        for (int s = 0; s < NBUF; s++) {
            mbar_init(bar_ofull + 8 * s, 12);
            mbar_init(bar_oempty + 8 * s, 1);
        }
        mbar_init(bar_wfree, 24);
        mbar_init(bar_wloc, 12);
        mbar_init(bar_spare, 1);
        mbar_init(bar_spare + 8, 1);
        sts(progress, 0);
        sts(total_slot, 0);
        sts(dry_slot, 0);
        asm volatile("fence.mbarrier_init.release.cluster;" ::: "memory");
        fence_async_smem();
        asm volatile("prefetch.tensormap [%0];" ::"l"(&tm_o) : "memory");
    }
    uint32_t t_entry = 0;
    if (tid == 448) {
        t_entry = now_ns();
        asm volatile("prefetch.tensormap [%0];" ::"l"(&tm_p) : "memory");
        l2_prefetch(x + ((size_t)cluster_id * (UNIT * TP) + rank * (TP / 2)) * C, STAGE_BYTES / 2);
    }
    __syncwarp();
    asm volatile("barrier.cluster.arrive.relaxed.aligned;" ::: "memory");

    if (wg == 3) {
        if (tid == 448) {
            while (now_ns() - t_entry < (uint32_t)X1_T) {}
            l2_prefetch(x + ((size_t)cluster_id * (UNIT * TP) + TP + rank * (TP / 2)) * C, STAGE_BYTES / 2);
        }
        __syncwarp();
        asm volatile("barrier.cluster.wait.aligned;" ::: "memory");
        if (tid == 384 && rank == 0) {
            const uint32_t peer = mapa(smem, 1) - smem;
            const int shallow = max(ntiles - SHALLOW * nclusters, STAGES * nclusters);
            int s = NLOCAL, n = 0;
            uint32_t ph = 1;
            int unit = cluster_id;
            for (int u = 0; unit < num_units; u++) {
                const bool late = unit >= num_units - 3 * nclusters;
                const unsigned long long t_fetch = late ? now_ns64() : 0;
                int next = unit - (NSTATIC - 1) * nclusters;
                if (u >= NSTATIC - 1) next = (int)atomicInc(&g_sched, (unsigned)(num_units - (NSTATIC - 1) * nclusters - 1));
#pragma unroll 1
                for (int h = 0; h < UNIT; h++, n++) {
                    if (n < NLOCAL) continue;
                    const int tile = unit * UNIT + h;
                    if (n == FREE_STAGES) mbar_wait(bar_wfree, 0);
                    mbar_wait(bar_empty + 8 * s, ph);
                    if (tile >= shallow) mbar_wait(bar_empty + 8 * ((s + 1) & 3), s == 3 ? ph ^ 1 : ph);
                    const uint32_t bar = bar_full + 8 * s;
                    tma_load_x_multicast(smem + s * STAGE_BYTES, &tm_x, tile, bar);
                    post_tile(bar, tile_slot + 4 * (n & 31), STAGE_BYTES + 4, tile);
                    post_tile(bar + peer, tile_slot + 4 * (n & 31) + peer, STAGE_BYTES + 4, tile);
                    sts_cluster(progress + peer, tile);
                    if (++s == STAGES) { s = 0; ph ^= 1; }
                    if (late && h == 0) {
                        asm volatile("" : "+r"(next)::"memory");
                        const int succ = next + NSTATIC * nclusters;
                        if (succ >= num_units) {
                            sts(total_slot, n + UNIT);
                            sts_cluster(total_slot + peer, n + UNIT);
                        }
                        if (succ == num_units - 1)
                            asm volatile("st.relaxed.gpu.global.b64 [%0], %1;" ::"l"(&g_dry), "l"(t_fetch) : "memory");
                    }
                }
                asm volatile("" : "+r"(next)::"memory");
                unit = next + NSTATIC * nclusters;
            }
            sts(total_slot, n);
            sts_cluster(total_slot + peer, n);
            sts_cluster(progress + peer, 0x7fffffff);
            mbar_wait(bar_empty + 8 * s, ph);
            post_tile(bar_full + 8 * s, tile_slot + 4 * (n & 31), 4, -1);
            post_tile(bar_full + 8 * s + peer, tile_slot + 4 * (n & 31) + peer, 4, -1);
#pragma unroll 1
            for (int e = 1; e < STAGES; e++) {
                if (++s == STAGES) { s = 0; ph ^= 1; }
                mbar_wait(bar_empty + 8 * s, ph);
            }
        } else if (tid == 448 && rank == 1) {
            auto wait_loader = [&](int tile) {
                while (lds(progress) < tile && now_ns() - t_entry < 1000000000u) __nanosleep(64);
            };
            const int slope = (RA_LEAD - RA_MIN) * 16 / (RA_END - RA_FADE);
            int lead = RA_LEAD * 16;
            uint32_t due = RA_T0 + cluster_id * RA_SKEW / nclusters;
#pragma unroll 1
            for (int j = NLOCAL; j * nclusters < ntiles; j++, due += RA_DT) {
                const int t = j < NSTATIC * UNIT ? (cluster_id + (j / UNIT) * nclusters) * UNIT + j % UNIT
                                                 : j * nclusters + cluster_id;
                if (j >= RA_FADE && j < RA_END) lead -= slope;
                wait_loader(t - (lead * nclusters >> 6));
                while (now_ns() - t_entry < due) {}
                if (t < ntiles) l2_prefetch_tile(&tm_p, t);
            }
            wait_loader(0x7fffffff);
        } else if (tid == 384 || tid == 448) {
            const unsigned long long t_start = now_ns64();
            for (uint32_t it = 0; it < (1u << 22); it++) {
                unsigned long long v;
                asm volatile("ld.relaxed.gpu.global.b64 %0, [%1];" : "=l"(v) : "l"(&g_dry) : "memory");
                if (v > t_start) { sts(dry_slot, (uint32_t)v | 1); break; }
                if (lds(dry_slot)) break;
                __nanosleep(200);
            }
        } else if ((tid & 63) == 32) {
            uint32_t base = smem;
            asm volatile("" : "+r"(base));
            const uint32_t ofull = base + (bar_ofull - smem), otile = base + (tile_slot - smem);
            const uint32_t total_at = base + (total_slot - smem);
            int k = (tid >> 6) & 1;
            auto wait_filled = [&](int j) -> bool {
                const uint32_t lap = (uint32_t)j / NBUF, bar = ofull + 8 * (j - lap * NBUF);
                for (uint32_t it = 0; it < (1u << 22); it++) {
                    if (mbar_try(bar, lap & 1)) return true;
                    const int total = lds(total_at);
                    if (total != 0 && j >= total) break;
                }
                return false;
            };
            auto test_filled = [&](int j) -> bool {
                const uint32_t lap = (uint32_t)j / NBUF;
                return mbar_test(ofull + 8 * (j - lap * NBUF), lap & 1);
            };
            const int skew = cluster_id & 1;
            auto trigger = [&]() -> int { return k + min((k + skew) * RAMP_Q >> 4, NBUF - 1); };
            auto store = [&]() -> int {
                const int tile = lds(otile + 4 * (k & 31));
                const uint32_t slot = (uint32_t)k % NBUF;
                tma_store_out(&tm_o, base + SMEM_OUT + slot * OUT_BYTES, rank * 3, tile);
                asm volatile("cp.async.bulk.wait_group.read 0;" ::: "memory");
                mbar_arrive(ofull + 8 * (NBUF + slot));
                k += 2;
                return tile;
            };
            const int near_end = ntiles - (KREG + 2 * NBUF) * nclusters;
            while (wait_filled(trigger()))
                if (store() >= near_end) break;
            uint32_t t_dry = 0, due = 0;
            for (uint32_t it = 0; it < (1u << 22); it++) {
                int total = lds(total_at);
                const int m = trigger();
                if ((total == 0 || m < total) && test_filled(m)) { store(); continue; }
                t_dry = lds(base + (dry_slot - smem));
                if (t_dry) {
                    if (total == 0) total = m + KREG + STAGES + DRAIN_PRE;
                    due = t_dry + max(DRAIN_T0, DRAIN_END - (total - k) * DRAIN_DT);
                    if ((int)(now_ns() - due) >= 0) break;
                } else if (total != 0 && total <= m + 1 && test_filled(total - 1)) {
                    break;
                }
            }
            if (!t_dry) {
                due = now_ns();
                t_dry = (due - DRAIN_END) | 1;
                sts(base + (dry_slot - smem), t_dry);
            }
            uint32_t prev = base + (bar_spare - smem) + 8 * (k & 1);
            while (true) {
                const int total = lds(total_at);
                if (total != 0) {
                    if (k >= total) break;
                    due = t_dry + DRAIN_END - (total - k) * DRAIN_DT;
                }
                if (!wait_filled(k)) break;
                const int tile = lds(otile + 4 * (k & 31));
                const uint32_t slot = (uint32_t)k % NBUF;
                while ((int)(now_ns() - due) < 0) {}
                tma_store_out(&tm_o, base + SMEM_OUT + slot * OUT_BYTES, rank * 3, tile);
                asm volatile("cp.async.bulk.wait_group.read 1;" ::: "memory");
                mbar_arrive(prev);
                prev = ofull + 8 * (NBUF + slot);
                k += 2;
                due += 2 * DRAIN_DT;
            }
            asm volatile("cp.async.bulk.wait_group.read 0;" ::: "memory");
        }
    } else {
        asm volatile("setmaxnreg.inc.sync.aligned.u32 160;");
        const int lane = tid & 31;
        const int warp = (tid >> 5) & 3;
        if (wg == 2) asm volatile("bar.arrive 8, 256;" ::: "memory");

        uint32_t bias2;
        {
            const unsigned short* bp =
                reinterpret_cast<const unsigned short*>(bias) + rank * 192 + wg * 64 + warp * 16 + (lane >> 2);
            const uint32_t b0 = bp[0], b1 = bp[8];
            bias2 = b0 | (b1 << 16);
        }
        const uint32_t swz = (uint32_t)(((warp * 2 + ((lane >> 3) & 1)) ^ (lane & 7)) << 4);
        const uint32_t lead = mapa(smem, 0) - smem;

        uint32_t a[24][4];
        asm volatile("barrier.cluster.wait.aligned;" ::: "memory");
        mbar_wait(bar_w + 8 * wg, 0);
        {
            const uint32_t base = smem + SMEM_W + wg * SLAB_BYTES + ((lane >> 4) * 8 + (lane & 7)) * 128 + swz;
#pragma unroll
            for (int ks = 0; ks < 24; ks++)
                asm volatile("ldmatrix.sync.aligned.m8n8.x4.trans.shared.b16 {%0,%1,%2,%3}, [%4];"
                             : "=r"(a[ks][0]), "=r"(a[ks][1]), "=r"(a[ks][2]), "=r"(a[ks][3])
                             : "r"(base + ks * 2048) : "memory");
        }
        fence_async_smem();
        __syncwarp();
        if (lane == 0) {
            mbar_arrive_cluster(bar_wfree + lead);
            mbar_arrive(bar_wloc);
        }

        uint32_t st_base = smem + SMEM_OUT + wg * 1024 + (lane >> 4) * 3072 + (lane & 7) * 128 + swz;
        const int wgu = __shfl_sync(0xffffffffu, wg, 0);
        asm volatile("" : "+r"(st_base), "+r"(bias2));
        const uint64_t desc0 = (uint64_t)((smem & 0x3FFFF) >> 4) | (1ull << 16) | ((6144ull >> 4) << 32) | (1ull << 62);

        int s = 0, ob = 0, i = 0;
        uint32_t ph = 0, oph = 1;
        float d[16];
        uint32_t q[KREG][8];
        auto compute = [&]() -> bool {
            mbar_wait(bar_full + 8 * s, ph);
            if (lds(tile_slot + 4 * (i & 31)) < 0) return false;
            const uint64_t desc = desc0 + (uint64_t)(s * (STAGE_BYTES >> 4));
            asm volatile("bar.sync %0, 256;" ::"r"(8 + wgu) : "memory");
            asm volatile("wgmma.fence.sync.aligned;" ::: "memory");
#pragma unroll
            for (int ks = 0; ks < 24; ks++) {
                wgmma_rs(d, a[ks], desc + (uint64_t)(((ks >> 2) * 1024 + (ks & 3) * 32) >> 4), ks != 0);
                if (ks == HANDOVER - 1) asm volatile("bar.arrive %0, 256;" ::"r"(wgu == 2 ? 8 : 9 + wgu) : "memory");
            }
            asm volatile("wgmma.commit_group.sync.aligned;" ::: "memory");
            asm volatile("wgmma.wait_group.sync.aligned 0;" ::: "memory");
#pragma unroll
            for (int j = 0; j < 16; j++) asm volatile("" : "+f"(d[j])::"memory");
            if (lane == 0) mbar_arrive_cluster(bar_empty + 8 * s + lead);
            if (++s == STAGES) { s = 0; ph ^= 1; }
            return true;
        };
        auto pack = [&](uint32_t (&p)[8]) {
#pragma unroll
            for (int j = 0; j < 8; j += 2) {
                p[j]     = cvt_add_bias<false>(d[2 * j], d[2 * j + 1], bias2);
                p[j + 1] = cvt_add_bias<true>(d[2 * j + 2], d[2 * j + 3], bias2);
            }
        };
        auto put = [&](uint32_t st, const uint32_t (&p)[8]) {
#pragma unroll
            for (int j = 0; j < 2; j++)
                asm volatile("stmatrix.sync.aligned.m8n8.x4.trans.shared.b16 [%0], {%1,%2,%3,%4};"
                             ::"r"(st + j * 6144), "r"(p[4 * j]), "r"(p[4 * j + 1]), "r"(p[4 * j + 2]), "r"(p[4 * j + 3])
                             : "memory");
        };
        auto acquire = [&]() -> uint32_t {
            mbar_wait(bar_oempty + 8 * ob, oph);
            return st_base + ob * OUT_BYTES;
        };
        auto publish = [&]() {
            fence_async_smem();
            __syncwarp();
            if (lane == 0) mbar_arrive(bar_ofull + 8 * ob);
            if (++ob == NBUF) { ob = 0; oph ^= 1; }
        };

        const int kstart = KSTART - cluster_id % KRAMP;
        int held = 0, h = 0;
        bool more = true;
#pragma unroll 1
        for (; i < kstart; i++) {
            more = compute();
            if (!more) break;
            pack(q[0]);
            if (i == 0) mbar_wait(bar_wloc, 0);
            put(acquire(), q[0]);
            publish();
        }
        if (more) {
            int kstep = kstart;
#pragma unroll 1
            for (; compute(); i++) {
                if (h == 0 && i >= kstep) {
#pragma unroll
                    for (int k = 0; k < KREG; k++)
                        if (held == k) pack(q[k]);
                    kstep = ++held == KREG ? 0x7fffffff : kstep + KRAMP;
                    continue;
                }
                const uint32_t st = acquire();
#pragma unroll
                for (int k = 0; k < KREG; k++)
                    if (h == k) { put(st, q[k]); pack(q[k]); }
                publish();
                if (++h == held) h = 0;
            }
#pragma unroll 1
            for (int left = held; left > 0; left--) {
                const uint32_t st = acquire();
#pragma unroll
                for (int k = 0; k < KREG; k++)
                    if (h == k) put(st, q[k]);
                publish();
                if (++h == held) h = 0;
            }
        }
        if (wg == 0) asm volatile("bar.sync 8, 256;" ::: "memory");
    }
}

typedef CUresult (*EncodeTiledFn)(CUtensorMap*, CUtensorMapDataType, cuuint32_t, void*, const cuuint64_t*,
                                  const cuuint64_t*, const cuuint32_t*, const cuuint32_t*, CUtensorMapInterleave,
                                  CUtensorMapSwizzle, CUtensorMapL2promotion, CUtensorMapFloatOOBfill);

void encode_map(EncodeTiledFn fn, CUtensorMap* tm, const void* ptr, int rank, const cuuint64_t* dims,
                const cuuint64_t* strides, const cuuint32_t* box) {
    const cuuint32_t estr[4] = {1, 1, 1, 1};
    fn(tm, CU_TENSOR_MAP_DATA_TYPE_BFLOAT16, rank, const_cast<void*>(ptr), dims, strides, box, estr,
       CU_TENSOR_MAP_INTERLEAVE_NONE, CU_TENSOR_MAP_SWIZZLE_128B, CU_TENSOR_MAP_L2_PROMOTION_L2_128B,
       CU_TENSOR_MAP_FLOAT_OOB_FILL_NONE);
}

}

extern "C" void kernel_launch(void* const* d_in, const int* in_sizes, int n_in, void* d_out, int out_size) {
    const __nv_bfloat16* x = (const __nv_bfloat16*)d_in[0];
    const __nv_bfloat16* w = (const __nv_bfloat16*)d_in[1];
    const __nv_bfloat16* b = (const __nv_bfloat16*)d_in[2];
    const int pixels = in_sizes[0] / C;

    static EncodeTiledFn encode = nullptr;
    static int max_clusters = 0;
    if (!encode) {
        void* fn = nullptr;
        cudaDriverEntryPointQueryResult qr;
        cudaGetDriverEntryPoint("cuTensorMapEncodeTiled", &fn, cudaEnableDefault, &qr);
        encode = (EncodeTiledFn)fn;
        cudaFuncSetAttribute(conv1x1_kernel, cudaFuncAttributeMaxDynamicSharedMemorySize, SMEM_TOTAL);
        cudaLaunchConfig_t cfg = {};
        cfg.gridDim = dim3(2, 1, 1);
        cfg.blockDim = dim3(NTHREADS, 1, 1);
        cfg.dynamicSmemBytes = SMEM_TOTAL;
        cudaLaunchAttribute at[1];
        at[0].id = cudaLaunchAttributeClusterDimension;
        at[0].val.clusterDim.x = 2; at[0].val.clusterDim.y = 1; at[0].val.clusterDim.z = 1;
        cfg.attrs = at; cfg.numAttrs = 1;
        if (cudaOccupancyMaxActiveClusters(&max_clusters, conv1x1_kernel, &cfg) != cudaSuccess || max_clusters <= 0) {
            (void)cudaGetLastError();
            int dev = 0, sms = 0;
            cudaGetDevice(&dev);
            cudaDeviceGetAttribute(&sms, cudaDevAttrMultiProcessorCount, dev);
            max_clusters = sms / 2;
        }
    }
    CUtensorMap tm_x, tm_w, tm_o, tm_p;
    {
        const cuuint64_t dims[4]    = {64, 8, 6, (cuuint64_t)(pixels / 8)};
        const cuuint64_t strides[3] = {C * 2, 128, C * 2 * 8};
        const cuuint32_t box_x[4]   = {64, 8, 6, TP / 8};
        const cuuint32_t box_o[4]   = {64, 8, 3, TP / 8};
        encode_map(encode, &tm_x, x, 4, dims, strides, box_x);
        encode_map(encode, &tm_o, d_out, 4, dims, strides, box_o);
        const cuuint64_t pdims[2]    = {64, (cuuint64_t)pixels * 6};
        const cuuint64_t pstrides[1] = {128};
        const cuuint32_t pbox[2]     = {64, STAGE_BYTES / 128};
        encode_map(encode, &tm_p, x, 2, pdims, pstrides, pbox);
        const cuuint64_t wdims[3]    = {C, 192, 2};
        const cuuint64_t wstrides[2] = {C * 2, C * 2 * 192};
        const cuuint32_t wbox[3]     = {64, 192, 2};
        encode_map(encode, &tm_w, w, 3, wdims, wstrides, wbox);
    }
    const int num_units = pixels / (TP * UNIT);
    const int nclusters = max_clusters * NSTATIC <= num_units ? max_clusters : num_units / NSTATIC;
    conv1x1_kernel<<<2 * nclusters, NTHREADS, SMEM_TOTAL, cudaStreamPerThread>>>(tm_x, tm_w, tm_o, tm_p, x, w, b, num_units);
}
```

```cpp
#include <cuda_runtime.h>
#include <cuda_bf16.h>
#include <cuda.h>
#include <stdint.h>

#define TUNE(name, value) constexpr int name = value
TUNE(RAMP_Q, 11);
TUNE(RAMP_0, -8);
TUNE(KSTART, 26);
TUNE(KRAMP, 3);
TUNE(X1_T, 400);
TUNE(RA_T0, 900);
TUNE(RA_DT, 468);
TUNE(RA_LEAD, 38);
TUNE(RA_FADE, 13);
TUNE(RA_END, 58);
TUNE(RA_MIN, 12);
TUNE(SHALLOW, 14);
TUNE(DRAIN_T0, 1400);
TUNE(DRAIN_END, 10900);
TUNE(DRAIN_DT, 481);
TUNE(DRAIN_PRE, 2);

namespace {

constexpr int C           = 384;
constexpr int TP          = 32;
constexpr int UNIT        = 2;
constexpr int NSTATIC     = 2;
constexpr int KREG        = 5;
constexpr int HANDOVER    = 18;
constexpr int STAGES      = 4;
constexpr int NBUF        = 10;
constexpr int NLOCAL      = 2;
constexpr int STAGE_BYTES = TP * C * 2;
constexpr int OUT_BYTES   = TP * 192 * 2;
constexpr int SLAB_BYTES  = C * 64 * 2;
constexpr int SMEM_OUT    = STAGES * STAGE_BYTES;
constexpr int SMEM_BAR    = SMEM_OUT + NBUF * OUT_BYTES;
constexpr int SMEM_TOTAL  = SMEM_BAR + 512 + 1024;
constexpr int NTHREADS    = 512;
constexpr int SMEM_W      = SMEM_BAR - 3 * SLAB_BYTES;
constexpr int FREE_STAGES = SMEM_W / STAGE_BYTES;
static_assert(SMEM_W % 1024 == 0 && NLOCAL <= FREE_STAGES && FREE_STAGES < NSTATIC * UNIT && NLOCAL <= UNIT, "layout");
static_assert(STAGES == 4, "the shallow mode of the loader assumes four stages");
static_assert(SMEM_TOTAL <= 232448, "too much shared memory");

__device__ unsigned int g_sched;
__device__ unsigned long long g_dry;

__device__ __forceinline__ uint32_t smem_u32(const void* p) { return (uint32_t)__cvta_generic_to_shared(p); }
__device__ __forceinline__ uint32_t now_ns() {
    uint32_t t;
    asm volatile("mov.u32 %0, %%globaltimer_lo;" : "=r"(t));
    return t;
}
__device__ __forceinline__ unsigned long long now_ns64() {
    unsigned long long t;
    asm volatile("mov.u64 %0, %%globaltimer;" : "=l"(t));
    return t;
}
__device__ __forceinline__ int lds(uint32_t addr) {
    int v;
    asm volatile("ld.volatile.shared.b32 %0, [%1];" : "=r"(v) : "r"(addr) : "memory");
    return v;
}
__device__ __forceinline__ void sts(uint32_t addr, int v) {
    asm volatile("st.volatile.shared.b32 [%0], %1;" ::"r"(addr), "r"(v) : "memory");
}
__device__ __forceinline__ void sts_cluster(uint32_t cluster_addr, int v) {
    asm volatile("st.volatile.shared::cluster.b32 [%0], %1;" ::"r"(cluster_addr), "r"(v) : "memory");
}
__device__ __forceinline__ void mbar_init(uint32_t bar, uint32_t count) {
    asm volatile("mbarrier.init.shared::cta.b64 [%0], %1;" ::"r"(bar), "r"(count) : "memory");
}
__device__ __forceinline__ void mbar_expect_tx(uint32_t bar, uint32_t bytes) {
    asm volatile("mbarrier.arrive.expect_tx.shared::cta.b64 _, [%0], %1;" ::"r"(bar), "r"(bytes) : "memory");
}
__device__ __forceinline__ void mbar_arrive(uint32_t bar) {
    asm volatile("mbarrier.arrive.shared::cta.b64 _, [%0];" ::"r"(bar) : "memory");
}
__device__ __forceinline__ void mbar_arrive_cluster(uint32_t cluster_addr) {
    asm volatile("mbarrier.arrive.shared::cluster.b64 _, [%0];" ::"r"(cluster_addr) : "memory");
}
__device__ __forceinline__ bool mbar_try(uint32_t bar, uint32_t parity) {
    uint32_t ok;
    asm volatile("{\n.reg .pred p;\nmbarrier.try_wait.parity.shared::cta.b64 p, [%1], %2;\nselp.u32 %0, 1, 0, p;\n}"
                 : "=r"(ok) : "r"(bar), "r"(parity) : "memory");
    return ok;
}
__device__ __forceinline__ bool mbar_test(uint32_t bar, uint32_t parity) {
    uint32_t ok;
    asm volatile("{\n.reg .pred p;\nmbarrier.test_wait.parity.shared::cta.b64 p, [%1], %2;\nselp.u32 %0, 1, 0, p;\n}"
                 : "=r"(ok) : "r"(bar), "r"(parity) : "memory");
    return ok;
}
__device__ __forceinline__ void mbar_wait(uint32_t bar, uint32_t parity) {
    asm volatile("{\n.reg .pred p, q;\n.reg .u32 n;\n"
                 "mbarrier.try_wait.parity.shared::cta.b64 p, [%0], %1;\n@p bra DONE;\nmov.u32 n, 0;\n"
                 "AGAIN:\nmbarrier.try_wait.parity.shared::cta.b64 p, [%0], %1;\nadd.u32 n, n, 1;\n"
                 "setp.lt.and.u32 q, n, 0x400000, !p;\n@q bra AGAIN;\nDONE:\n}"
                 ::"r"(bar), "r"(parity) : "memory");
}
__device__ __forceinline__ uint32_t mapa(uint32_t addr, uint32_t rank) {
    uint32_t r;
    asm("mapa.shared::cluster.u32 %0, %1, %2;" : "=r"(r) : "r"(addr), "r"(rank));
    return r;
}
__device__ __forceinline__ void fence_async_smem() { asm volatile("fence.proxy.async.shared::cta;" ::: "memory"); }
__device__ __forceinline__ void post_tile(uint32_t bar, uint32_t slot, uint32_t bytes, int value) {
    asm volatile("mbarrier.arrive.expect_tx.shared::cluster.b64 _, [%0], %1;" ::"r"(bar), "r"(bytes) : "memory");
    asm volatile("st.async.weak.shared::cluster.mbarrier::complete_tx::bytes.b32 [%0], %1, [%2];"
                 ::"r"(slot), "r"(value), "r"(bar) : "memory");
}
__device__ __forceinline__ void tma_load_w(uint32_t dst, const CUtensorMap* tm, int ch, uint32_t bar) {
    asm volatile("cp.async.bulk.tensor.3d.shared::cluster.global.mbarrier::complete_tx::bytes [%0], [%1, {%3, %4, %4}], [%2];"
                 ::"r"(dst), "l"(tm), "r"(bar), "r"(ch), "r"(0) : "memory");
}
__device__ __forceinline__ void tma_load_x(uint32_t dst, const CUtensorMap* tm, int tile, uint32_t bar) {
    asm volatile("cp.async.bulk.tensor.4d.shared::cluster.global.mbarrier::complete_tx::bytes"
                 " [%0], [%1, {%4, %4, %4, %3}], [%2];"
                 ::"r"(dst), "l"(tm), "r"(bar), "r"(tile * (TP / 8)), "r"(0) : "memory");
}
__device__ __forceinline__ void tma_load_x_multicast(uint32_t dst, const CUtensorMap* tm, int tile, uint32_t bar) {
    asm volatile("cp.async.bulk.tensor.4d.shared::cluster.global.mbarrier::complete_tx::bytes.multicast::cluster"
                 " [%0], [%1, {%4, %4, %4, %3}], [%2], %5;"
                 ::"r"(dst), "l"(tm), "r"(bar), "r"(tile * (TP / 8)), "r"(0), "h"((uint16_t)3) : "memory");
}
__device__ __forceinline__ void tma_store_out(const CUtensorMap* tm, uint32_t src, int slab, int tile) {
    asm volatile("cp.async.bulk.tensor.4d.global.shared::cta.bulk_group [%0, {%4, %4, %2, %3}], [%1];"
                 ::"l"(tm), "r"(src), "r"(slab), "r"(tile * (TP / 8)), "r"(0) : "memory");
    asm volatile("cp.async.bulk.commit_group;" ::: "memory");
}
__device__ __forceinline__ void l2_prefetch(const void* p, uint32_t bytes) {
    asm volatile("cp.async.bulk.prefetch.L2.global [%0], %1;" ::"l"(p), "r"(bytes) : "memory");
}

__device__ __forceinline__ void l2_prefetch_tile(const CUtensorMap* tm, int tile) {
    asm volatile("cp.async.bulk.prefetch.tensor.2d.L2.global.tile [%0, {%1, %2}];"
                 ::"l"(tm), "r"(0), "r"(tile * (STAGE_BYTES / 128)) : "memory");
}

__device__ __forceinline__ void wgmma_rs(float (&d)[16], const uint32_t (&a)[4], uint64_t desc, int scale_d) {
    asm volatile(
        "{\n.reg .pred p;\nsetp.ne.b32 p, %21, 0;\n"
        "wgmma.mma_async.sync.aligned.m64n32k16.f32.bf16.bf16 "
        "{%0,%1,%2,%3,%4,%5,%6,%7,%8,%9,%10,%11,%12,%13,%14,%15},"
        "{%16,%17,%18,%19}, %20, p, 1, 1, 0;\n}"
        : "+f"(d[0]), "+f"(d[1]), "+f"(d[2]), "+f"(d[3]), "+f"(d[4]), "+f"(d[5]), "+f"(d[6]), "+f"(d[7]),
          "+f"(d[8]), "+f"(d[9]), "+f"(d[10]), "+f"(d[11]), "+f"(d[12]), "+f"(d[13]), "+f"(d[14]), "+f"(d[15])
        : "r"(a[0]), "r"(a[1]), "r"(a[2]), "r"(a[3]), "l"(desc), "r"(scale_d));
}
template <bool HI>
__device__ __forceinline__ uint32_t cvt_add_bias(float lo, float hi, uint32_t bias2) {
    uint32_t r;
    if (HI) asm("{\n.reg .b32 t, b;\n.reg .b16 l, h;\ncvt.rn.bf16x2.f32 t, %2, %1;\nmov.b32 {l, h}, %3;\nmov.b32 b, {h, h};\n"
                "add.rn.bf16x2 %0, t, b;\n}" : "=r"(r) : "f"(lo), "f"(hi), "r"(bias2));
    else asm("{\n.reg .b32 t, b;\n.reg .b16 l, h;\ncvt.rn.bf16x2.f32 t, %2, %1;\nmov.b32 {l, h}, %3;\nmov.b32 b, {l, l};\n"
             "add.rn.bf16x2 %0, t, b;\n}" : "=r"(r) : "f"(lo), "f"(hi), "r"(bias2));
    return r;
}

__global__ void __cluster_dims__(2, 1, 1) __launch_bounds__(NTHREADS, 1)
conv1x1_kernel(const __nv_bfloat16* __restrict__ x, const __nv_bfloat16* __restrict__ w,
               const __nv_bfloat16* __restrict__ bias, int num_units,
               const __grid_constant__ CUtensorMap tm_x, const __grid_constant__ CUtensorMap tm_w,
               const __grid_constant__ CUtensorMap tm_o, const __grid_constant__ CUtensorMap tm_p) {
    extern __shared__ uint8_t smem_raw[];
    const uint32_t smem = (smem_u32(smem_raw) + 1023u) & ~1023u;
    const uint32_t bar_full   = smem + SMEM_BAR;
    const uint32_t bar_empty  = bar_full + 8 * STAGES;
    const uint32_t bar_ofull  = bar_empty + 8 * STAGES;
    const uint32_t bar_oempty = bar_ofull + 8 * NBUF;
    const uint32_t bar_w      = bar_oempty + 8 * NBUF;
    const uint32_t bar_wfree  = bar_w + 24;
    const uint32_t bar_wloc   = bar_wfree + 8;
    const uint32_t bar_spare  = bar_wloc + 8;
    const uint32_t progress   = bar_spare + 16;
    const uint32_t total_slot = progress + 4;
    const uint32_t dry_slot   = progress + 8;
    const uint32_t tile_slot  = progress + 16;

    const int tid = threadIdx.x;
    const int wg  = tid >> 7;
    uint32_t rank;
    asm("mov.u32 %0, %%cluster_ctarank;" : "=r"(rank));
    const int cluster_id = blockIdx.x >> 1;
    const int nclusters  = gridDim.x >> 1;
    const int ntiles     = num_units * UNIT;

    asm volatile("setmaxnreg.dec.sync.aligned.u32 32;");

    uint32_t t_entry = 0;
    if (tid == 448) {
        if (blockIdx.x < 128) l2_prefetch(w + blockIdx.x * (C * C / 128), C * C * 2 / 128);
        l2_prefetch(x + (size_t)(cluster_id * (UNIT * TP) + rank * (TP / 2)) * C, STAGE_BYTES / 2);
        t_entry = now_ns();
        asm volatile("prefetch.tensormap [%0];" ::"l"(&tm_p) : "memory");
    }
    if (tid == 384) {
        asm volatile("prefetch.tensormap [%0];" ::"l"(&tm_w) : "memory");
        asm volatile("prefetch.tensormap [%0];" ::"l"(&tm_x) : "memory");
        for (int g = 0; g < 3; g++) mbar_init(bar_w + 8 * g, 1);
        for (int s = 0; s < NLOCAL; s++) mbar_init(bar_full + 8 * s, 1);
        asm volatile("fence.mbarrier_init.release.cluster;" ::: "memory");
        fence_async_smem();
        for (int g = 0; g < 3; g++) {
            mbar_expect_tx(bar_w + 8 * g, SLAB_BYTES);
            tma_load_w(smem + SMEM_W + g * SLAB_BYTES, &tm_w, rank * 192 + g * 64, bar_w + 8 * g);
        }
        for (int s = 0; s < NLOCAL; s++) {
            sts(tile_slot + 4 * s, cluster_id * UNIT + s);
            mbar_expect_tx(bar_full + 8 * s, STAGE_BYTES);
            tma_load_x(smem + s * STAGE_BYTES, &tm_x, cluster_id * UNIT + s, bar_full + 8 * s);
        }
    }
    if (tid == 416) {
        for (int s = NLOCAL; s < STAGES; s++) mbar_init(bar_full + 8 * s, 1);
        for (int s = 0; s < STAGES; s++) mbar_init(bar_empty + 8 * s, 24);
        for (int s = 0; s < NBUF; s++) {
            mbar_init(bar_ofull + 8 * s, 12);
            mbar_init(bar_oempty + 8 * s, 1);
        }
        mbar_init(bar_wfree, 24);
        mbar_init(bar_wloc, 12);
        mbar_init(bar_spare, 1);
        mbar_init(bar_spare + 8, 1);
        sts(progress, 0);
        sts(total_slot, 0);
        sts(dry_slot, 0);
        asm volatile("fence.mbarrier_init.release.cluster;" ::: "memory");
        fence_async_smem();
        asm volatile("prefetch.tensormap [%0];" ::"l"(&tm_o) : "memory");
    }
    __syncwarp();
    asm volatile("barrier.cluster.arrive.relaxed.aligned;" ::: "memory");

    if (wg == 3) {
        if (tid == 448) {
            while (now_ns() - t_entry < (uint32_t)X1_T) {}
            l2_prefetch(x + ((size_t)cluster_id * (UNIT * TP) + TP + rank * (TP / 2)) * C, STAGE_BYTES / 2);
        }
        __syncwarp();
        asm volatile("barrier.cluster.wait.aligned;" ::: "memory");
        if (tid == 384 && rank == 0) {
            const uint32_t peer = mapa(smem, 1) - smem;
            const int shallow = max(ntiles - SHALLOW * nclusters, STAGES * nclusters);
            int s = NLOCAL, n = 0;
            uint32_t ph = 1;
            int unit = cluster_id;
            for (int u = 0; unit < num_units; u++) {
                const bool late = unit >= num_units - 3 * nclusters;
                const unsigned long long t_fetch = late ? now_ns64() : 0;
                int next = unit - (NSTATIC - 1) * nclusters;
                if (u >= NSTATIC - 1) next = (int)atomicInc(&g_sched, (unsigned)(num_units - (NSTATIC - 1) * nclusters - 1));
#pragma unroll 1
                for (int h = 0; h < UNIT; h++, n++) {
                    if (n < NLOCAL) continue;
                    const int tile = unit * UNIT + h;
                    if (n == FREE_STAGES) mbar_wait(bar_wfree, 0);
                    mbar_wait(bar_empty + 8 * s, ph);
                    if (tile >= shallow) mbar_wait(bar_empty + 8 * ((s + 1) & 3), s == 3 ? ph ^ 1 : ph);
                    const uint32_t bar = bar_full + 8 * s;
                    tma_load_x_multicast(smem + s * STAGE_BYTES, &tm_x, tile, bar);
                    post_tile(bar, tile_slot + 4 * (n & 31), STAGE_BYTES + 4, tile);
                    post_tile(bar + peer, tile_slot + 4 * (n & 31) + peer, STAGE_BYTES + 4, tile);
                    sts_cluster(progress + peer, tile);
                    if (++s == STAGES) { s = 0; ph ^= 1; }
                    if (late && h == 0) {
                        asm volatile("" : "+r"(next)::"memory");
                        const int succ = next + NSTATIC * nclusters;
                        if (succ >= num_units) {
                            sts(total_slot, n + UNIT);
                            sts_cluster(total_slot + peer, n + UNIT);
                        }
                        if (succ == num_units - 1)
                            asm volatile("st.relaxed.gpu.global.b64 [%0], %1;" ::"l"(&g_dry), "l"(t_fetch) : "memory");
                    }
                }
                asm volatile("" : "+r"(next)::"memory");
                unit = next + NSTATIC * nclusters;
            }
            sts(total_slot, n);
            sts_cluster(total_slot + peer, n);
            sts_cluster(progress + peer, 0x7fffffff);
            mbar_wait(bar_empty + 8 * s, ph);
            post_tile(bar_full + 8 * s, tile_slot + 4 * (n & 31), 4, -1);
            post_tile(bar_full + 8 * s + peer, tile_slot + 4 * (n & 31) + peer, 4, -1);
#pragma unroll 1
            for (int e = 1; e < STAGES; e++) {
                if (++s == STAGES) { s = 0; ph ^= 1; }
                mbar_wait(bar_empty + 8 * s, ph);
            }
        } else if (tid == 448 && rank == 1) {
            auto wait_loader = [&](int tile) {
                while (lds(progress) < tile && now_ns() - t_entry < 1000000000u) __nanosleep(64);
            };
            const int slope = (RA_LEAD - RA_MIN) * 16 / (RA_END - RA_FADE);
            int lead = RA_LEAD * 16;
            uint32_t due = RA_T0;
#pragma unroll 1
            for (int j = NLOCAL; j * nclusters < ntiles; j++, due += RA_DT) {
                const int t = j < NSTATIC * UNIT ? (cluster_id + (j / UNIT) * nclusters) * UNIT + j % UNIT
                                                 : j * nclusters + cluster_id;
                if (j >= RA_FADE && j < RA_END) lead -= slope;
                wait_loader(t - (lead * nclusters >> 6));
                while (now_ns() - t_entry < due) {}
                if (t < ntiles) l2_prefetch_tile(&tm_p, t);
            }
            wait_loader(0x7fffffff);
        } else if (tid == 384 || tid == 448) {
            const unsigned long long t_start = now_ns64();
            for (uint32_t it = 0; it < (1u << 22); it++) {
                unsigned long long v;
                asm volatile("ld.relaxed.gpu.global.b64 %0, [%1];" : "=l"(v) : "l"(&g_dry) : "memory");
                if (v > t_start) { sts(dry_slot, (uint32_t)v | 1); break; }
                if (lds(dry_slot)) break;
                __nanosleep(200);
            }
        } else if ((tid & 63) == 32) {
            uint32_t base = smem;
            asm volatile("" : "+r"(base));
            const uint32_t ofull = base + (bar_ofull - smem), otile = base + (tile_slot - smem);
            const uint32_t total_at = base + (total_slot - smem);
            int k = (tid >> 6) & 1;
            auto wait_filled = [&](int j) -> bool {
                const uint32_t lap = (uint32_t)j / NBUF, bar = ofull + 8 * (j - lap * NBUF);
                for (uint32_t it = 0; it < (1u << 22); it++) {
                    if (mbar_try(bar, lap & 1)) return true;
                    const int total = lds(total_at);
                    if (total != 0 && j >= total) break;
                }
                return false;
            };
            auto test_filled = [&](int j) -> bool {
                const uint32_t lap = (uint32_t)j / NBUF;
                return mbar_test(ofull + 8 * (j - lap * NBUF), lap & 1);
            };
            const int skew = cluster_id & 1;
            auto trigger = [&]() -> int { return k + min(max(0, RAMP_0 + (k + skew) * RAMP_Q) >> 4, NBUF - 1); };
            auto store = [&]() -> int {
                const int tile = lds(otile + 4 * (k & 31));
                const uint32_t slot = (uint32_t)k % NBUF;
                tma_store_out(&tm_o, base + SMEM_OUT + slot * OUT_BYTES, rank * 3, tile);
                asm volatile("cp.async.bulk.wait_group.read 0;" ::: "memory");
                mbar_arrive(ofull + 8 * (NBUF + slot));
                k += 2;
                return tile;
            };
            const int near_end = ntiles - (KREG + 2 * NBUF) * nclusters;
            while (wait_filled(trigger()))
                if (store() >= near_end) break;
            uint32_t t_dry = 0, due = 0;
            for (uint32_t it = 0; it < (1u << 22); it++) {
                int total = lds(total_at);
                const int m = trigger();
                if ((total == 0 || m < total) && test_filled(m)) { store(); continue; }
                t_dry = lds(base + (dry_slot - smem));
                if (t_dry) {
                    if (total == 0) total = m + KREG + STAGES + DRAIN_PRE;
                    due = t_dry + max(DRAIN_T0, DRAIN_END - (total - k) * DRAIN_DT);
                    if ((int)(now_ns() - due) >= 0) break;
                } else if (total != 0 && total <= m + 1 && test_filled(total - 1)) {
                    break;
                }
            }
            if (!t_dry) {
                due = now_ns();
                t_dry = (due - DRAIN_END) | 1;
                sts(base + (dry_slot - smem), t_dry);
            }
            uint32_t prev = base + (bar_spare - smem) + 8 * (k & 1);
            while (true) {
                const int total = lds(total_at);
                if (total != 0) {
                    if (k >= total) break;
                    due = t_dry + DRAIN_END - (total - k) * DRAIN_DT;
                }
                if (!wait_filled(k)) break;
                const int tile = lds(otile + 4 * (k & 31));
                const uint32_t slot = (uint32_t)k % NBUF;
                while ((int)(now_ns() - due) < 0) {}
                tma_store_out(&tm_o, base + SMEM_OUT + slot * OUT_BYTES, rank * 3, tile);
                asm volatile("cp.async.bulk.wait_group.read 1;" ::: "memory");
                mbar_arrive(prev);
                prev = ofull + 8 * (NBUF + slot);
                k += 2;
                due += 2 * DRAIN_DT;
            }
            asm volatile("cp.async.bulk.wait_group.read 0;" ::: "memory");
        }
    } else {
        asm volatile("setmaxnreg.inc.sync.aligned.u32 160;");
        const int lane = tid & 31;
        const int warp = (tid >> 5) & 3;
        if (wg == 2) asm volatile("bar.arrive 8, 256;" ::: "memory");

        uint32_t bias2;
        {
            const unsigned short* bp =
                reinterpret_cast<const unsigned short*>(bias) + rank * 192 + wg * 64 + warp * 16 + (lane >> 2);
            const uint32_t b0 = bp[0], b1 = bp[8];
            bias2 = b0 | (b1 << 16);
        }
        const uint32_t swz = (uint32_t)(((warp * 2 + ((lane >> 3) & 1)) ^ (lane & 7)) << 4);
        const uint32_t lead = mapa(smem, 0) - smem;

        uint32_t a[24][4];
        asm volatile("barrier.cluster.wait.aligned;" ::: "memory");
        mbar_wait(bar_w + 8 * wg, 0);
        {
            const uint32_t base = smem + SMEM_W + wg * SLAB_BYTES + ((lane >> 4) * 8 + (lane & 7)) * 128 + swz;
#pragma unroll
            for (int ks = 0; ks < 24; ks++)
                asm volatile("ldmatrix.sync.aligned.m8n8.x4.trans.shared.b16 {%0,%1,%2,%3}, [%4];"
                             : "=r"(a[ks][0]), "=r"(a[ks][1]), "=r"(a[ks][2]), "=r"(a[ks][3])
                             : "r"(base + ks * 2048) : "memory");
        }
        fence_async_smem();
        __syncwarp();
        if (lane == 0) {
            mbar_arrive_cluster(bar_wfree + lead);
            mbar_arrive(bar_wloc);
        }

        uint32_t st_base = smem + SMEM_OUT + wg * 1024 + (lane >> 4) * 3072 + (lane & 7) * 128 + swz;
        const int wgu = __shfl_sync(0xffffffffu, wg, 0);
        asm volatile("" : "+r"(st_base), "+r"(bias2));
        const uint64_t desc0 = (uint64_t)((smem & 0x3FFFF) >> 4) | (1ull << 16) | ((6144ull >> 4) << 32) | (1ull << 62);

        int s = 0, ob = 0, i = 0;
        uint32_t ph = 0, oph = 1;
        float d[16];
        uint32_t q[KREG][8];
        auto compute = [&]() -> bool {
            mbar_wait(bar_full + 8 * s, ph);
            if (lds(tile_slot + 4 * (i & 31)) < 0) return false;
            const uint64_t desc = desc0 + (uint64_t)(s * (STAGE_BYTES >> 4));
            asm volatile("bar.sync %0, 256;" ::"r"(8 + wgu) : "memory");
            asm volatile("wgmma.fence.sync.aligned;" ::: "memory");
#pragma unroll
            for (int ks = 0; ks < 24; ks++) {
                wgmma_rs(d, a[ks], desc + (uint64_t)(((ks >> 2) * 1024 + (ks & 3) * 32) >> 4), ks != 0);
                if (ks == HANDOVER - 1) asm volatile("bar.arrive %0, 256;" ::"r"(wgu == 2 ? 8 : 9 + wgu) : "memory");
            }
            asm volatile("wgmma.commit_group.sync.aligned;" ::: "memory");
            asm volatile("wgmma.wait_group.sync.aligned 0;" ::: "memory");
#pragma unroll
            for (int j = 0; j < 16; j++) asm volatile("" : "+f"(d[j])::"memory");
            if (lane == 0) mbar_arrive_cluster(bar_empty + 8 * s + lead);
            if (++s == STAGES) { s = 0; ph ^= 1; }
            return true;
        };
        auto pack = [&](uint32_t (&p)[8]) {
#pragma unroll
            for (int j = 0; j < 8; j += 2) {
                p[j]     = cvt_add_bias<false>(d[2 * j], d[2 * j + 1], bias2);
                p[j + 1] = cvt_add_bias<true>(d[2 * j + 2], d[2 * j + 3], bias2);
            }
        };
        auto put = [&](uint32_t st, const uint32_t (&p)[8]) {
#pragma unroll
            for (int j = 0; j < 2; j++)
                asm volatile("stmatrix.sync.aligned.m8n8.x4.trans.shared.b16 [%0], {%1,%2,%3,%4};"
                             ::"r"(st + j * 6144), "r"(p[4 * j]), "r"(p[4 * j + 1]), "r"(p[4 * j + 2]), "r"(p[4 * j + 3])
                             : "memory");
        };
        auto acquire = [&]() -> uint32_t {
            mbar_wait(bar_oempty + 8 * ob, oph);
            return st_base + ob * OUT_BYTES;
        };
        auto publish = [&]() {
            fence_async_smem();
            __syncwarp();
            if (lane == 0) mbar_arrive(bar_ofull + 8 * ob);
            if (++ob == NBUF) { ob = 0; oph ^= 1; }
        };

        const int kstart = KSTART - cluster_id % KRAMP;
        int held = 0, h = 0;
        bool more = true;
#pragma unroll 1
        for (; i < kstart; i++) {
            more = compute();
            if (!more) break;
            pack(q[0]);
            if (i == 0) mbar_wait(bar_wloc, 0);
            put(acquire(), q[0]);
            publish();
        }
        if (more) {
            int kstep = kstart;
#pragma unroll 1
            for (; compute(); i++) {
                if (h == 0 && i >= kstep) {
#pragma unroll
                    for (int k = 0; k < KREG; k++)
                        if (held == k) pack(q[k]);
                    kstep = ++held == KREG ? 0x7fffffff : kstep + KRAMP;
                    continue;
                }
                const uint32_t st = acquire();
#pragma unroll
                for (int k = 0; k < KREG; k++)
                    if (h == k) { put(st, q[k]); pack(q[k]); }
                publish();
                if (++h == held) h = 0;
            }
#pragma unroll 1
            for (int left = held; left > 0; left--) {
                const uint32_t st = acquire();
#pragma unroll
                for (int k = 0; k < KREG; k++)
                    if (h == k) put(st, q[k]);
                publish();
                if (++h == held) h = 0;
            }
        }
        if (wg == 0) asm volatile("bar.sync 8, 256;" ::: "memory");
    }
}

typedef CUresult (*EncodeTiledFn)(CUtensorMap*, CUtensorMapDataType, cuuint32_t, void*, const cuuint64_t*,
                                  const cuuint64_t*, const cuuint32_t*, const cuuint32_t*, CUtensorMapInterleave,
                                  CUtensorMapSwizzle, CUtensorMapL2promotion, CUtensorMapFloatOOBfill);

void encode_map(EncodeTiledFn fn, CUtensorMap* tm, const void* ptr, int rank, const cuuint64_t* dims,
                const cuuint64_t* strides, const cuuint32_t* box) {
    const cuuint32_t estr[4] = {1, 1, 1, 1};
    fn(tm, CU_TENSOR_MAP_DATA_TYPE_BFLOAT16, rank, const_cast<void*>(ptr), dims, strides, box, estr,
       CU_TENSOR_MAP_INTERLEAVE_NONE, CU_TENSOR_MAP_SWIZZLE_128B, CU_TENSOR_MAP_L2_PROMOTION_L2_128B,
       CU_TENSOR_MAP_FLOAT_OOB_FILL_NONE);
}

}

extern "C" void kernel_launch(void* const* d_in, const int* in_sizes, int n_in, void* d_out, int out_size) {
    const __nv_bfloat16* x = (const __nv_bfloat16*)d_in[0];
    const __nv_bfloat16* w = (const __nv_bfloat16*)d_in[1];
    const __nv_bfloat16* b = (const __nv_bfloat16*)d_in[2];
    const int pixels = in_sizes[0] / C;

    static EncodeTiledFn encode = nullptr;
    static int max_clusters = 0;
    if (!encode) {
        void* fn = nullptr;
        cudaDriverEntryPointQueryResult qr;
        cudaGetDriverEntryPoint("cuTensorMapEncodeTiled", &fn, cudaEnableDefault, &qr);
        encode = (EncodeTiledFn)fn;
        cudaFuncSetAttribute(conv1x1_kernel, cudaFuncAttributeMaxDynamicSharedMemorySize, SMEM_TOTAL);
        cudaLaunchConfig_t cfg = {};
        cfg.gridDim = dim3(2, 1, 1);
        cfg.blockDim = dim3(NTHREADS, 1, 1);
        cfg.dynamicSmemBytes = SMEM_TOTAL;
        cudaLaunchAttribute at[1];
        at[0].id = cudaLaunchAttributeClusterDimension;
        at[0].val.clusterDim.x = 2; at[0].val.clusterDim.y = 1; at[0].val.clusterDim.z = 1;
        cfg.attrs = at; cfg.numAttrs = 1;
        if (cudaOccupancyMaxActiveClusters(&max_clusters, conv1x1_kernel, &cfg) != cudaSuccess || max_clusters <= 0) {
            (void)cudaGetLastError();
            int dev = 0, sms = 0;
            cudaGetDevice(&dev);
            cudaDeviceGetAttribute(&sms, cudaDevAttrMultiProcessorCount, dev);
            max_clusters = sms / 2;
        }
    }
    CUtensorMap tm_x, tm_w, tm_o, tm_p;
    {
        const cuuint64_t dims[4]    = {64, 8, 6, (cuuint64_t)(pixels / 8)};
        const cuuint64_t strides[3] = {C * 2, 128, C * 2 * 8};
        const cuuint32_t box_x[4]   = {64, 8, 6, TP / 8};
        const cuuint32_t box_o[4]   = {64, 8, 3, TP / 8};
        encode_map(encode, &tm_x, x, 4, dims, strides, box_x);
        encode_map(encode, &tm_o, d_out, 4, dims, strides, box_o);
        const cuuint64_t pdims[2]    = {64, (cuuint64_t)pixels * 6};
        const cuuint64_t pstrides[1] = {128};
        const cuuint32_t pbox[2]     = {64, STAGE_BYTES / 128};
        encode_map(encode, &tm_p, x, 2, pdims, pstrides, pbox);
        const cuuint64_t wdims[3]    = {C, 192, 2};
        const cuuint64_t wstrides[2] = {C * 2, C * 2 * 192};
        const cuuint32_t wbox[3]     = {64, 192, 2};
        encode_map(encode, &tm_w, w, 3, wdims, wstrides, wbox);
    }
    const int num_units = pixels / (TP * UNIT);
    const int nclusters = max_clusters * NSTATIC <= num_units ? max_clusters : num_units / NSTATIC;
    conv1x1_kernel<<<2 * nclusters, NTHREADS, SMEM_TOTAL, cudaStreamPerThread>>>(x, w, b, num_units, tm_x, tm_w, tm_o, tm_p);
}
```

```cpp
#include <cuda_runtime.h>
#include <cuda_bf16.h>
#include <cuda.h>
#include <stdint.h>

#define TUNE(name, value) constexpr int name = value
TUNE(RAMP_Q, 11);
TUNE(RAMP_0, -8);
TUNE(KSTART, 26);
TUNE(KRAMP, 3);
TUNE(X1_T, 300);
TUNE(RA_T0, 850);
TUNE(RA_DT, 473);
TUNE(RA_LEAD, 40);
TUNE(RA_FADE, 9);
TUNE(RA_END, 61);
TUNE(RA_MIN, 11);
TUNE(SHALLOW, 12);
TUNE(DRAIN_T0, 950);
TUNE(DRAIN_END, 10900);
TUNE(DRAIN_DT, 465);
TUNE(DRAIN_PRE, 2);

namespace {

constexpr int C           = 384;
constexpr int TP          = 32;
constexpr int UNIT        = 2;
constexpr int NSTATIC     = 2;
constexpr int KREG        = 5;
constexpr int HANDOVER    = 18;
constexpr int STAGES      = 4;
constexpr int NBUF        = 10;
constexpr int NLOCAL      = 2;
constexpr int STAGE_BYTES = TP * C * 2;
constexpr int OUT_BYTES   = TP * 192 * 2;
constexpr int SLAB_BYTES  = C * 64 * 2;
constexpr int SMEM_OUT    = STAGES * STAGE_BYTES;
constexpr int SMEM_BAR    = SMEM_OUT + NBUF * OUT_BYTES;
constexpr int SMEM_TOTAL  = SMEM_BAR + 512 + 1024;
constexpr int NTHREADS    = 512;
constexpr int SMEM_W      = SMEM_BAR - 3 * SLAB_BYTES;
constexpr int FREE_STAGES = SMEM_W / STAGE_BYTES;
static_assert(SMEM_W % 1024 == 0 && NLOCAL <= FREE_STAGES && FREE_STAGES < NSTATIC * UNIT && NLOCAL <= UNIT, "layout");
static_assert(STAGES == 4, "the shallow mode of the loader assumes four stages");
static_assert(SMEM_TOTAL <= 232448, "too much shared memory");

__device__ unsigned int g_sched;
__device__ unsigned long long g_dry;

__device__ __forceinline__ uint32_t smem_u32(const void* p) { return (uint32_t)__cvta_generic_to_shared(p); }
__device__ __forceinline__ uint32_t now_ns() {
    uint32_t t;
    asm volatile("mov.u32 %0, %%globaltimer_lo;" : "=r"(t));
    return t;
}
__device__ __forceinline__ unsigned long long now_ns64() {
    unsigned long long t;
    asm volatile("mov.u64 %0, %%globaltimer;" : "=l"(t));
    return t;
}
__device__ __forceinline__ int lds(uint32_t addr) {
    int v;
    asm volatile("ld.volatile.shared.b32 %0, [%1];" : "=r"(v) : "r"(addr) : "memory");
    return v;
}
__device__ __forceinline__ void sts(uint32_t addr, int v) {
    asm volatile("st.volatile.shared.b32 [%0], %1;" ::"r"(addr), "r"(v) : "memory");
}
__device__ __forceinline__ void sts_cluster(uint32_t cluster_addr, int v) {
    asm volatile("st.volatile.shared::cluster.b32 [%0], %1;" ::"r"(cluster_addr), "r"(v) : "memory");
}
__device__ __forceinline__ void mbar_init(uint32_t bar, uint32_t count) {
    asm volatile("mbarrier.init.shared::cta.b64 [%0], %1;" ::"r"(bar), "r"(count) : "memory");
}
__device__ __forceinline__ void mbar_expect_tx(uint32_t bar, uint32_t bytes) {
    asm volatile("mbarrier.arrive.expect_tx.shared::cta.b64 _, [%0], %1;" ::"r"(bar), "r"(bytes) : "memory");
}
__device__ __forceinline__ void mbar_arrive(uint32_t bar) {
    asm volatile("mbarrier.arrive.shared::cta.b64 _, [%0];" ::"r"(bar) : "memory");
}
__device__ __forceinline__ void mbar_arrive_cluster(uint32_t cluster_addr) {
    asm volatile("mbarrier.arrive.shared::cluster.b64 _, [%0];" ::"r"(cluster_addr) : "memory");
}
__device__ __forceinline__ bool mbar_try(uint32_t bar, uint32_t parity) {
    uint32_t ok;
    asm volatile("{\n.reg .pred p;\nmbarrier.try_wait.parity.shared::cta.b64 p, [%1], %2;\nselp.u32 %0, 1, 0, p;\n}"
                 : "=r"(ok) : "r"(bar), "r"(parity) : "memory");
    return ok;
}
__device__ __forceinline__ bool mbar_test(uint32_t bar, uint32_t parity) {
    uint32_t ok;
    asm volatile("{\n.reg .pred p;\nmbarrier.test_wait.parity.shared::cta.b64 p, [%1], %2;\nselp.u32 %0, 1, 0, p;\n}"
                 : "=r"(ok) : "r"(bar), "r"(parity) : "memory");
    return ok;
}
__device__ __forceinline__ void mbar_wait(uint32_t bar, uint32_t parity) {
    asm volatile("{\n.reg .pred p, q;\n.reg .u32 n;\n"
                 "mbarrier.try_wait.parity.shared::cta.b64 p, [%0], %1;\n@p bra DONE;\nmov.u32 n, 0;\n"
                 "AGAIN:\nmbarrier.try_wait.parity.shared::cta.b64 p, [%0], %1;\nadd.u32 n, n, 1;\n"
                 "setp.lt.and.u32 q, n, 0x400000, !p;\n@q bra AGAIN;\nDONE:\n}"
                 ::"r"(bar), "r"(parity) : "memory");
}
__device__ __forceinline__ uint32_t mapa(uint32_t addr, uint32_t rank) {
    uint32_t r;
    asm("mapa.shared::cluster.u32 %0, %1, %2;" : "=r"(r) : "r"(addr), "r"(rank));
    return r;
}
__device__ __forceinline__ void fence_async_smem() { asm volatile("fence.proxy.async.shared::cta;" ::: "memory"); }
__device__ __forceinline__ void post_tile(uint32_t bar, uint32_t slot, uint32_t bytes, int value) {
    asm volatile("mbarrier.arrive.expect_tx.shared::cluster.b64 _, [%0], %1;" ::"r"(bar), "r"(bytes) : "memory");
    asm volatile("st.async.weak.shared::cluster.mbarrier::complete_tx::bytes.b32 [%0], %1, [%2];"
                 ::"r"(slot), "r"(value), "r"(bar) : "memory");
}
__device__ __forceinline__ void tma_load_w(uint32_t dst, const CUtensorMap* tm, int ch, uint32_t bar) {
    asm volatile("cp.async.bulk.tensor.3d.shared::cluster.global.mbarrier::complete_tx::bytes [%0], [%1, {%3, %4, %4}], [%2];"
                 ::"r"(dst), "l"(tm), "r"(bar), "r"(ch), "r"(0) : "memory");
}
__device__ __forceinline__ void tma_load_x(uint32_t dst, const CUtensorMap* tm, int tile, uint32_t bar) {
    asm volatile("cp.async.bulk.tensor.4d.shared::cluster.global.mbarrier::complete_tx::bytes"
                 " [%0], [%1, {%4, %4, %4, %3}], [%2];"
                 ::"r"(dst), "l"(tm), "r"(bar), "r"(tile * (TP / 8)), "r"(0) : "memory");
}
__device__ __forceinline__ void tma_load_x_multicast(uint32_t dst, const CUtensorMap* tm, int tile, uint32_t bar) {
    asm volatile("cp.async.bulk.tensor.4d.shared::cluster.global.mbarrier::complete_tx::bytes.multicast::cluster"
                 " [%0], [%1, {%4, %4, %4, %3}], [%2], %5;"
                 ::"r"(dst), "l"(tm), "r"(bar), "r"(tile * (TP / 8)), "r"(0), "h"((uint16_t)3) : "memory");
}
__device__ __forceinline__ void tma_store_out(const CUtensorMap* tm, uint32_t src, int slab, int tile) {
    asm volatile("cp.async.bulk.tensor.4d.global.shared::cta.bulk_group [%0, {%4, %4, %2, %3}], [%1];"
                 ::"l"(tm), "r"(src), "r"(slab), "r"(tile * (TP / 8)), "r"(0) : "memory");
    asm volatile("cp.async.bulk.commit_group;" ::: "memory");
}
__device__ __forceinline__ void l2_prefetch(const void* p, uint32_t bytes) {
    asm volatile("cp.async.bulk.prefetch.L2.global [%0], %1;" ::"l"(p), "r"(bytes) : "memory");
}

__device__ __forceinline__ void l2_prefetch_tile(const CUtensorMap* tm, int tile) {
    asm volatile("cp.async.bulk.prefetch.tensor.2d.L2.global.tile [%0, {%1, %2}];"
                 ::"l"(tm), "r"(0), "r"(tile * (STAGE_BYTES / 128)) : "memory");
}

__device__ __forceinline__ void wgmma_rs(float (&d)[16], const uint32_t (&a)[4], uint64_t desc, int scale_d) {
    asm volatile(
        "{\n.reg .pred p;\nsetp.ne.b32 p, %21, 0;\n"
        "wgmma.mma_async.sync.aligned.m64n32k16.f32.bf16.bf16 "
        "{%0,%1,%2,%3,%4,%5,%6,%7,%8,%9,%10,%11,%12,%13,%14,%15},"
        "{%16,%17,%18,%19}, %20, p, 1, 1, 0;\n}"
        : "+f"(d[0]), "+f"(d[1]), "+f"(d[2]), "+f"(d[3]), "+f"(d[4]), "+f"(d[5]), "+f"(d[6]), "+f"(d[7]),
          "+f"(d[8]), "+f"(d[9]), "+f"(d[10]), "+f"(d[11]), "+f"(d[12]), "+f"(d[13]), "+f"(d[14]), "+f"(d[15])
        : "r"(a[0]), "r"(a[1]), "r"(a[2]), "r"(a[3]), "l"(desc), "r"(scale_d));
}
template <bool HI>
__device__ __forceinline__ uint32_t cvt_add_bias(float lo, float hi, uint32_t bias2) {
    uint32_t r;
    if (HI) asm("{\n.reg .b32 t, b;\n.reg .b16 l, h;\ncvt.rn.bf16x2.f32 t, %2, %1;\nmov.b32 {l, h}, %3;\nmov.b32 b, {h, h};\n"
                "add.rn.bf16x2 %0, t, b;\n}" : "=r"(r) : "f"(lo), "f"(hi), "r"(bias2));
    else asm("{\n.reg .b32 t, b;\n.reg .b16 l, h;\ncvt.rn.bf16x2.f32 t, %2, %1;\nmov.b32 {l, h}, %3;\nmov.b32 b, {l, l};\n"
             "add.rn.bf16x2 %0, t, b;\n}" : "=r"(r) : "f"(lo), "f"(hi), "r"(bias2));
    return r;
}

__global__ void __cluster_dims__(2, 1, 1) __launch_bounds__(NTHREADS, 1)
conv1x1_kernel(const __nv_bfloat16* __restrict__ x, const __nv_bfloat16* __restrict__ w,
               const __nv_bfloat16* __restrict__ bias, int num_units,
               const __grid_constant__ CUtensorMap tm_x, const __grid_constant__ CUtensorMap tm_w,
               const __grid_constant__ CUtensorMap tm_o, const __grid_constant__ CUtensorMap tm_p) {
    extern __shared__ uint8_t smem_raw[];
    const uint32_t smem = (smem_u32(smem_raw) + 1023u) & ~1023u;
    const uint32_t bar_full   = smem + SMEM_BAR;
    const uint32_t bar_empty  = bar_full + 8 * STAGES;
    const uint32_t bar_ofull  = bar_empty + 8 * STAGES;
    const uint32_t bar_oempty = bar_ofull + 8 * NBUF;
    const uint32_t bar_w      = bar_oempty + 8 * NBUF;
    const uint32_t bar_wfree  = bar_w + 24;
    const uint32_t bar_wloc   = bar_wfree + 8;
    const uint32_t bar_spare  = bar_wloc + 8;
    const uint32_t progress   = bar_spare + 16;
    const uint32_t total_slot = progress + 4;
    const uint32_t dry_slot   = progress + 8;
    const uint32_t tile_slot  = progress + 16;

    const int tid = threadIdx.x;
    const int wg  = tid >> 7;
    uint32_t rank;
    asm("mov.u32 %0, %%cluster_ctarank;" : "=r"(rank));
    const int cluster_id = blockIdx.x >> 1;
    const int nclusters  = gridDim.x >> 1;
    const int ntiles     = num_units * UNIT;

    asm volatile("setmaxnreg.dec.sync.aligned.u32 32;");

    uint32_t t_entry = 0;
    if (tid == 448) {
        if (blockIdx.x < 128) l2_prefetch(w + blockIdx.x * (C * C / 128), C * C * 2 / 128);
        l2_prefetch(x + (size_t)(cluster_id * (UNIT * TP) + rank * (TP / 2)) * C, STAGE_BYTES / 2);
        t_entry = now_ns();
        asm volatile("prefetch.tensormap [%0];" ::"l"(&tm_p) : "memory");
    }
    if (tid == 384) {
        asm volatile("prefetch.tensormap [%0];" ::"l"(&tm_w) : "memory");
        asm volatile("prefetch.tensormap [%0];" ::"l"(&tm_x) : "memory");
        for (int g = 0; g < 3; g++) mbar_init(bar_w + 8 * g, 1);
        for (int s = 0; s < NLOCAL; s++) mbar_init(bar_full + 8 * s, 1);
        asm volatile("fence.mbarrier_init.release.cluster;" ::: "memory");
        fence_async_smem();
        for (int g = 0; g < 3; g++) {
            mbar_expect_tx(bar_w + 8 * g, SLAB_BYTES);
            tma_load_w(smem + SMEM_W + g * SLAB_BYTES, &tm_w, rank * 192 + g * 64, bar_w + 8 * g);
        }
        for (int s = 0; s < NLOCAL; s++) {
            sts(tile_slot + 4 * s, cluster_id * UNIT + s);
            mbar_expect_tx(bar_full + 8 * s, STAGE_BYTES);
            tma_load_x(smem + s * STAGE_BYTES, &tm_x, cluster_id * UNIT + s, bar_full + 8 * s);
        }
    }
    if (tid == 416) {
        for (int s = NLOCAL; s < STAGES; s++) mbar_init(bar_full + 8 * s, 1);
        for (int s = 0; s < STAGES; s++) mbar_init(bar_empty + 8 * s, 24);
        for (int s = 0; s < NBUF; s++) {
            mbar_init(bar_ofull + 8 * s, 12);
            mbar_init(bar_oempty + 8 * s, 1);
        }
        mbar_init(bar_wfree, 24);
        mbar_init(bar_wloc, 12);
        mbar_init(bar_spare, 1);
        mbar_init(bar_spare + 8, 1);
        sts(progress, 0);
        sts(total_slot, 0);
        sts(dry_slot, 0);
        asm volatile("fence.mbarrier_init.release.cluster;" ::: "memory");
        fence_async_smem();
        asm volatile("prefetch.tensormap [%0];" ::"l"(&tm_o) : "memory");
    }
    __syncwarp();
    asm volatile("barrier.cluster.arrive.relaxed.aligned;" ::: "memory");

    if (wg == 3) {
        if (tid == 448) {
            while (now_ns() - t_entry < (uint32_t)X1_T) {}
            l2_prefetch(x + ((size_t)cluster_id * (UNIT * TP) + TP + rank * (TP / 2)) * C, STAGE_BYTES / 2);
        }
        __syncwarp();
        asm volatile("barrier.cluster.wait.aligned;" ::: "memory");
        if (tid == 384 && rank == 0) {
            const uint32_t peer = mapa(smem, 1) - smem;
            const int shallow = max(ntiles - SHALLOW * nclusters, STAGES * nclusters);
            int s = NLOCAL, n = 0;
            uint32_t ph = 1;
            int unit = cluster_id;
            for (int u = 0; unit < num_units; u++) {
                const bool late = unit >= num_units - 3 * nclusters;
                const unsigned long long t_fetch = late ? now_ns64() : 0;
                int next = unit - (NSTATIC - 1) * nclusters;
                if (u >= NSTATIC - 1) next = (int)atomicInc(&g_sched, (unsigned)(num_units - (NSTATIC - 1) * nclusters - 1));
#pragma unroll 1
                for (int h = 0; h < UNIT; h++, n++) {
                    if (n < NLOCAL) continue;
                    const int tile = unit * UNIT + h;
                    if (n == FREE_STAGES) mbar_wait(bar_wfree, 0);
                    mbar_wait(bar_empty + 8 * s, ph);
                    if (tile >= shallow) mbar_wait(bar_empty + 8 * ((s + 1) & 3), s == 3 ? ph ^ 1 : ph);
                    const uint32_t bar = bar_full + 8 * s;
                    tma_load_x_multicast(smem + s * STAGE_BYTES, &tm_x, tile, bar);
                    post_tile(bar, tile_slot + 4 * (n & 31), STAGE_BYTES + 4, tile);
                    post_tile(bar + peer, tile_slot + 4 * (n & 31) + peer, STAGE_BYTES + 4, tile);
                    sts_cluster(progress + peer, tile);
                    if (++s == STAGES) { s = 0; ph ^= 1; }
                    if (late && h == 0) {
                        asm volatile("" : "+r"(next)::"memory");
                        const int succ = next + NSTATIC * nclusters;
                        if (succ >= num_units) {
                            sts(total_slot, n + UNIT);
                            sts_cluster(total_slot + peer, n + UNIT);
                        }
                        if (succ == num_units - 1)
                            asm volatile("st.relaxed.gpu.global.b64 [%0], %1;" ::"l"(&g_dry), "l"(t_fetch) : "memory");
                    }
                }
                asm volatile("" : "+r"(next)::"memory");
                unit = next + NSTATIC * nclusters;
            }
            sts(total_slot, n);
            sts_cluster(total_slot + peer, n);
            sts_cluster(progress + peer, 0x7fffffff);
            mbar_wait(bar_empty + 8 * s, ph);
            post_tile(bar_full + 8 * s, tile_slot + 4 * (n & 31), 4, -1);
            post_tile(bar_full + 8 * s + peer, tile_slot + 4 * (n & 31) + peer, 4, -1);
#pragma unroll 1
            for (int e = 1; e < STAGES; e++) {
                if (++s == STAGES) { s = 0; ph ^= 1; }
                mbar_wait(bar_empty + 8 * s, ph);
            }
        } else if (tid == 448 && rank == 1) {
            auto wait_loader = [&](int tile) {
                while (lds(progress) < tile && now_ns() - t_entry < 1000000000u) __nanosleep(64);
            };
            const int slope = (RA_LEAD - RA_MIN) * 256 / (RA_END - RA_FADE);
            int lead = RA_LEAD * 256;
            uint32_t due = RA_T0;
#pragma unroll 1
            for (int j = NLOCAL; j * nclusters < ntiles; j++, due += RA_DT) {
                const int t = j < NSTATIC * UNIT ? (cluster_id + (j / UNIT) * nclusters) * UNIT + j % UNIT
                                                 : j * nclusters + cluster_id;
                if (j >= RA_FADE && j < RA_END) lead -= slope;
                wait_loader(t - (lead * nclusters >> 10));
                while (now_ns() - t_entry < due) {}
                if (t < ntiles) l2_prefetch_tile(&tm_p, t);
            }
            wait_loader(0x7fffffff);
        } else if (tid == 384 || tid == 448) {
            const unsigned long long t_start = now_ns64();
            for (uint32_t it = 0; it < (1u << 22); it++) {
                unsigned long long v;
                asm volatile("ld.relaxed.gpu.global.b64 %0, [%1];" : "=l"(v) : "l"(&g_dry) : "memory");
                if (v > t_start) { sts(dry_slot, (uint32_t)v | 1); break; }
                if (lds(dry_slot)) break;
                __nanosleep(200);
            }
        } else if ((tid & 63) == 32) {
            uint32_t base = smem;
            asm volatile("" : "+r"(base));
            const uint32_t ofull = base + (bar_ofull - smem), otile = base + (tile_slot - smem);
            const uint32_t total_at = base + (total_slot - smem);
            int k = (tid >> 6) & 1;
            auto wait_filled = [&](int j) -> bool {
                const uint32_t lap = (uint32_t)j / NBUF, bar = ofull + 8 * (j - lap * NBUF);
                for (uint32_t it = 0; it < (1u << 22); it++) {
                    if (mbar_try(bar, lap & 1)) return true;
                    const int total = lds(total_at);
                    if (total != 0 && j >= total) break;
                }
                return false;
            };
            auto test_filled = [&](int j) -> bool {
                const uint32_t lap = (uint32_t)j / NBUF;
                return mbar_test(ofull + 8 * (j - lap * NBUF), lap & 1);
            };
            const int skew = cluster_id & 1;
            auto trigger = [&]() -> int { return k + min(max(0, RAMP_0 + (k + skew) * RAMP_Q) >> 4, NBUF - 1); };
            auto store = [&]() -> int {
                const int tile = lds(otile + 4 * (k & 31));
                const uint32_t slot = (uint32_t)k % NBUF;
                tma_store_out(&tm_o, base + SMEM_OUT + slot * OUT_BYTES, rank * 3, tile);
                asm volatile("cp.async.bulk.wait_group.read 0;" ::: "memory");
                mbar_arrive(ofull + 8 * (NBUF + slot));
                k += 2;
                return tile;
            };
            const int near_end = ntiles - (KREG + 2 * NBUF) * nclusters;
            while (wait_filled(trigger()))
                if (store() >= near_end) break;
            uint32_t t_dry = 0, due = 0;
            for (uint32_t it = 0; it < (1u << 22); it++) {
                int total = lds(total_at);
                const int m = trigger();
                if ((total == 0 || m < total) && test_filled(m)) { store(); continue; }
                t_dry = lds(base + (dry_slot - smem));
                if (t_dry) {
                    if (total == 0) total = m + KREG + STAGES + DRAIN_PRE;
                    due = t_dry + max(DRAIN_T0, DRAIN_END - (total - k) * DRAIN_DT);
                    if ((int)(now_ns() - due) >= 0) break;
                } else if (total != 0 && total <= m + 1 && test_filled(total - 1)) {
                    break;
                }
            }
            if (!t_dry) {
                due = now_ns();
                t_dry = (due - DRAIN_END) | 1;
                sts(base + (dry_slot - smem), t_dry);
            }
            uint32_t prev = base + (bar_spare - smem) + 8 * (k & 1);
            while (true) {
                const int total = lds(total_at);
                if (total != 0) {
                    if (k >= total) break;
                    due = t_dry + DRAIN_END - (total - k) * DRAIN_DT;
                }
                if (!wait_filled(k)) break;
                const int tile = lds(otile + 4 * (k & 31));
                const uint32_t slot = (uint32_t)k % NBUF;
                while ((int)(now_ns() - due) < 0) {}
                tma_store_out(&tm_o, base + SMEM_OUT + slot * OUT_BYTES, rank * 3, tile);
                asm volatile("cp.async.bulk.wait_group.read 1;" ::: "memory");
                mbar_arrive(prev);
                prev = ofull + 8 * (NBUF + slot);
                k += 2;
                due += 2 * DRAIN_DT;
            }
            asm volatile("cp.async.bulk.wait_group.read 0;" ::: "memory");
        }
    } else {
        asm volatile("setmaxnreg.inc.sync.aligned.u32 160;");
        const int lane = tid & 31;
        const int warp = (tid >> 5) & 3;
        if (wg == 2) asm volatile("bar.arrive 8, 256;" ::: "memory");

        uint32_t bias2;
        {
            const unsigned short* bp =
                reinterpret_cast<const unsigned short*>(bias) + rank * 192 + wg * 64 + warp * 16 + (lane >> 2);
            const uint32_t b0 = bp[0], b1 = bp[8];
            bias2 = b0 | (b1 << 16);
        }
        const uint32_t swz = (uint32_t)(((warp * 2 + ((lane >> 3) & 1)) ^ (lane & 7)) << 4);
        const uint32_t lead = mapa(smem, 0) - smem;

        uint32_t a[24][4];
        asm volatile("barrier.cluster.wait.aligned;" ::: "memory");
        mbar_wait(bar_w + 8 * wg, 0);
        {
            const uint32_t base = smem + SMEM_W + wg * SLAB_BYTES + ((lane >> 4) * 8 + (lane & 7)) * 128 + swz;
#pragma unroll
            for (int ks = 0; ks < 24; ks++)
                asm volatile("ldmatrix.sync.aligned.m8n8.x4.trans.shared.b16 {%0,%1,%2,%3}, [%4];"
                             : "=r"(a[ks][0]), "=r"(a[ks][1]), "=r"(a[ks][2]), "=r"(a[ks][3])
                             : "r"(base + ks * 2048) : "memory");
        }
        fence_async_smem();
        __syncwarp();
        if (lane == 0) {
            mbar_arrive_cluster(bar_wfree + lead);
            mbar_arrive(bar_wloc);
        }

        uint32_t st_base = smem + SMEM_OUT + wg * 1024 + (lane >> 4) * 3072 + (lane & 7) * 128 + swz;
        const int wgu = __shfl_sync(0xffffffffu, wg, 0);
        asm volatile("" : "+r"(st_base), "+r"(bias2));
        const uint64_t desc0 = (uint64_t)((smem & 0x3FFFF) >> 4) | (1ull << 16) | ((6144ull >> 4) << 32) | (1ull << 62);

        int s = 0, ob = 0, i = 0;
        uint32_t ph = 0, oph = 1;
        float d[16];
        uint32_t q[KREG][8];
        auto compute = [&]() -> bool {
            mbar_wait(bar_full + 8 * s, ph);
            if (lds(tile_slot + 4 * (i & 31)) < 0) return false;
            const uint64_t desc = desc0 + (uint64_t)(s * (STAGE_BYTES >> 4));
            asm volatile("bar.sync %0, 256;" ::"r"(8 + wgu) : "memory");
            asm volatile("wgmma.fence.sync.aligned;" ::: "memory");
#pragma unroll
            for (int ks = 0; ks < 24; ks++) {
                wgmma_rs(d, a[ks], desc + (uint64_t)(((ks >> 2) * 1024 + (ks & 3) * 32) >> 4), ks != 0);
                if (ks == HANDOVER - 1) asm volatile("bar.arrive %0, 256;" ::"r"(wgu == 2 ? 8 : 9 + wgu) : "memory");
            }
            asm volatile("wgmma.commit_group.sync.aligned;" ::: "memory");
            asm volatile("wgmma.wait_group.sync.aligned 0;" ::: "memory");
#pragma unroll
            for (int j = 0; j < 16; j++) asm volatile("" : "+f"(d[j])::"memory");
            if (lane == 0) mbar_arrive_cluster(bar_empty + 8 * s + lead);
            if (++s == STAGES) { s = 0; ph ^= 1; }
            return true;
        };
        auto pack = [&](uint32_t (&p)[8]) {
#pragma unroll
            for (int j = 0; j < 8; j += 2) {
                p[j]     = cvt_add_bias<false>(d[2 * j], d[2 * j + 1], bias2);
                p[j + 1] = cvt_add_bias<true>(d[2 * j + 2], d[2 * j + 3], bias2);
            }
        };
        auto put = [&](uint32_t st, const uint32_t (&p)[8]) {
#pragma unroll
            for (int j = 0; j < 2; j++)
                asm volatile("stmatrix.sync.aligned.m8n8.x4.trans.shared.b16 [%0], {%1,%2,%3,%4};"
                             ::"r"(st + j * 6144), "r"(p[4 * j]), "r"(p[4 * j + 1]), "r"(p[4 * j + 2]), "r"(p[4 * j + 3])
                             : "memory");
        };
        auto acquire = [&]() -> uint32_t {
            mbar_wait(bar_oempty + 8 * ob, oph);
            return st_base + ob * OUT_BYTES;
        };
        auto publish = [&]() {
            fence_async_smem();
            __syncwarp();
            if (lane == 0) mbar_arrive(bar_ofull + 8 * ob);
            if (++ob == NBUF) { ob = 0; oph ^= 1; }
        };

        const int kstart = KSTART - cluster_id % KRAMP;
        int held = 0, h = 0;
        bool more = true;
#pragma unroll 1
        for (; i < kstart; i++) {
            more = compute();
            if (!more) break;
            pack(q[0]);
            if (i == 0) mbar_wait(bar_wloc, 0);
            put(acquire(), q[0]);
            publish();
        }
        if (more) {
            int kstep = kstart;
#pragma unroll 1
            for (; compute(); i++) {
                if (h == 0 && i >= kstep) {
#pragma unroll
                    for (int k = 0; k < KREG; k++)
                        if (held == k) pack(q[k]);
                    kstep = ++held == KREG ? 0x7fffffff : kstep + KRAMP;
                    continue;
                }
                const uint32_t st = acquire();
#pragma unroll
                for (int k = 0; k < KREG; k++)
                    if (h == k) { put(st, q[k]); pack(q[k]); }
                publish();
                if (++h == held) h = 0;
            }
#pragma unroll 1
            for (int left = held; left > 0; left--) {
                const uint32_t st = acquire();
#pragma unroll
                for (int k = 0; k < KREG; k++)
                    if (h == k) put(st, q[k]);
                publish();
                if (++h == held) h = 0;
            }
        }
        if (wg == 0) asm volatile("bar.sync 8, 256;" ::: "memory");
    }
}

typedef CUresult (*EncodeTiledFn)(CUtensorMap*, CUtensorMapDataType, cuuint32_t, void*, const cuuint64_t*,
                                  const cuuint64_t*, const cuuint32_t*, const cuuint32_t*, CUtensorMapInterleave,
                                  CUtensorMapSwizzle, CUtensorMapL2promotion, CUtensorMapFloatOOBfill);

void encode_map(EncodeTiledFn fn, CUtensorMap* tm, const void* ptr, int rank, const cuuint64_t* dims,
                const cuuint64_t* strides, const cuuint32_t* box) {
    const cuuint32_t estr[4] = {1, 1, 1, 1};
    fn(tm, CU_TENSOR_MAP_DATA_TYPE_BFLOAT16, rank, const_cast<void*>(ptr), dims, strides, box, estr,
       CU_TENSOR_MAP_INTERLEAVE_NONE, CU_TENSOR_MAP_SWIZZLE_128B, CU_TENSOR_MAP_L2_PROMOTION_L2_128B,
       CU_TENSOR_MAP_FLOAT_OOB_FILL_NONE);
}

}

extern "C" void kernel_launch(void* const* d_in, const int* in_sizes, int n_in, void* d_out, int out_size) {
    const __nv_bfloat16* x = (const __nv_bfloat16*)d_in[0];
    const __nv_bfloat16* w = (const __nv_bfloat16*)d_in[1];
    const __nv_bfloat16* b = (const __nv_bfloat16*)d_in[2];
    const int pixels = in_sizes[0] / C;

    static EncodeTiledFn encode = nullptr;
    static int max_clusters = 0;
    if (!encode) {
        void* fn = nullptr;
        cudaDriverEntryPointQueryResult qr;
        cudaGetDriverEntryPoint("cuTensorMapEncodeTiled", &fn, cudaEnableDefault, &qr);
        encode = (EncodeTiledFn)fn;
        cudaFuncSetAttribute(conv1x1_kernel, cudaFuncAttributeMaxDynamicSharedMemorySize, SMEM_TOTAL);
        cudaLaunchConfig_t cfg = {};
        cfg.gridDim = dim3(2, 1, 1);
        cfg.blockDim = dim3(NTHREADS, 1, 1);
        cfg.dynamicSmemBytes = SMEM_TOTAL;
        cudaLaunchAttribute at[1];
        at[0].id = cudaLaunchAttributeClusterDimension;
        at[0].val.clusterDim.x = 2; at[0].val.clusterDim.y = 1; at[0].val.clusterDim.z = 1;
        cfg.attrs = at; cfg.numAttrs = 1;
        if (cudaOccupancyMaxActiveClusters(&max_clusters, conv1x1_kernel, &cfg) != cudaSuccess || max_clusters <= 0) {
            (void)cudaGetLastError();
            int dev = 0, sms = 0;
            cudaGetDevice(&dev);
            cudaDeviceGetAttribute(&sms, cudaDevAttrMultiProcessorCount, dev);
            max_clusters = sms / 2;
        }
    }
    CUtensorMap tm_x, tm_w, tm_o, tm_p;
    {
        const cuuint64_t dims[4]    = {64, 8, 6, (cuuint64_t)(pixels / 8)};
        const cuuint64_t strides[3] = {C * 2, 128, C * 2 * 8};
        const cuuint32_t box_x[4]   = {64, 8, 6, TP / 8};
        const cuuint32_t box_o[4]   = {64, 8, 3, TP / 8};
        encode_map(encode, &tm_x, x, 4, dims, strides, box_x);
        encode_map(encode, &tm_o, d_out, 4, dims, strides, box_o);
        const cuuint64_t pdims[2]    = {64, (cuuint64_t)pixels * 6};
        const cuuint64_t pstrides[1] = {128};
        const cuuint32_t pbox[2]     = {64, STAGE_BYTES / 128};
        encode_map(encode, &tm_p, x, 2, pdims, pstrides, pbox);
        const cuuint64_t wdims[3]    = {C, 192, 2};
        const cuuint64_t wstrides[2] = {C * 2, C * 2 * 192};
        const cuuint32_t wbox[3]     = {64, 192, 2};
        encode_map(encode, &tm_w, w, 3, wdims, wstrides, wbox);
    }
    const int num_units = pixels / (TP * UNIT);
    const int nclusters = max_clusters * NSTATIC <= num_units ? max_clusters : num_units / NSTATIC;
    conv1x1_kernel<<<2 * nclusters, NTHREADS, SMEM_TOTAL, cudaStreamPerThread>>>(x, w, b, num_units, tm_x, tm_w, tm_o, tm_p);
}
```

```cpp
#include <cuda_runtime.h>
#include <cuda_bf16.h>
#include <cuda.h>
#include <stdint.h>

#define TUNE(name, value) constexpr int name = value
TUNE(RAMP_Q, 11);
TUNE(RAMP_0, -8);
TUNE(KSTART, 26);
TUNE(KRAMP, 3);
TUNE(X1_T, 300);
TUNE(RA_T0, 850);
TUNE(RA_DT, 473);
TUNE(RA_LEAD, 40);
TUNE(RA_FADE, 9);
TUNE(RA_END, 61);
TUNE(RA_MIN, 9);
TUNE(SHALLOW, 9);
TUNE(DRAIN_T0, 950);
TUNE(DRAIN_END, 10900);
TUNE(DRAIN_DT, 465);
TUNE(DRAIN_PRE, 2);

namespace {

constexpr int C           = 384;
constexpr int TP          = 32;
constexpr int UNIT        = 2;
constexpr int NSTATIC     = 2;
constexpr int KREG        = 5;
constexpr int HANDOVER    = 18;
constexpr int STAGES      = 4;
constexpr int NBUF        = 10;
constexpr int NLOCAL      = 2;
constexpr int STAGE_BYTES = TP * C * 2;
constexpr int OUT_BYTES   = TP * 192 * 2;
constexpr int SLAB_BYTES  = C * 64 * 2;
constexpr int SMEM_OUT    = STAGES * STAGE_BYTES;
constexpr int SMEM_BAR    = SMEM_OUT + NBUF * OUT_BYTES;
constexpr int SMEM_TOTAL  = SMEM_BAR + 512 + 1024;
constexpr int NTHREADS    = 512;
constexpr int SMEM_W      = SMEM_BAR - 3 * SLAB_BYTES;
constexpr int FREE_STAGES = SMEM_W / STAGE_BYTES;
static_assert(SMEM_W % 1024 == 0 && NLOCAL <= FREE_STAGES && FREE_STAGES < NSTATIC * UNIT && NLOCAL <= UNIT, "layout");
static_assert(STAGES == 4, "the shallow mode of the loader assumes four stages");
static_assert(SMEM_TOTAL <= 232448, "too much shared memory");

__device__ unsigned int g_sched;
__device__ unsigned long long g_dry;

__device__ __forceinline__ uint32_t smem_u32(const void* p) { return (uint32_t)__cvta_generic_to_shared(p); }
__device__ __forceinline__ uint32_t now_ns() {
    uint32_t t;
    asm volatile("mov.u32 %0, %%globaltimer_lo;" : "=r"(t));
    return t;
}
__device__ __forceinline__ unsigned long long now_ns64() {
    unsigned long long t;
    asm volatile("mov.u64 %0, %%globaltimer;" : "=l"(t));
    return t;
}
__device__ __forceinline__ int lds(uint32_t addr) {
    int v;
    asm volatile("ld.volatile.shared.b32 %0, [%1];" : "=r"(v) : "r"(addr) : "memory");
    return v;
}
__device__ __forceinline__ void sts(uint32_t addr, int v) {
    asm volatile("st.volatile.shared.b32 [%0], %1;" ::"r"(addr), "r"(v) : "memory");
}
__device__ __forceinline__ void sts_cluster(uint32_t cluster_addr, int v) {
    asm volatile("st.volatile.shared::cluster.b32 [%0], %1;" ::"r"(cluster_addr), "r"(v) : "memory");
}
__device__ __forceinline__ void mbar_init(uint32_t bar, uint32_t count) {
    asm volatile("mbarrier.init.shared::cta.b64 [%0], %1;" ::"r"(bar), "r"(count) : "memory");
}
__device__ __forceinline__ void mbar_expect_tx(uint32_t bar, uint32_t bytes) {
    asm volatile("mbarrier.arrive.expect_tx.shared::cta.b64 _, [%0], %1;" ::"r"(bar), "r"(bytes) : "memory");
}
__device__ __forceinline__ void mbar_arrive(uint32_t bar) {
    asm volatile("mbarrier.arrive.shared::cta.b64 _, [%0];" ::"r"(bar) : "memory");
}
__device__ __forceinline__ void mbar_arrive_cluster(uint32_t cluster_addr) {
    asm volatile("mbarrier.arrive.shared::cluster.b64 _, [%0];" ::"r"(cluster_addr) : "memory");
}
__device__ __forceinline__ bool mbar_try(uint32_t bar, uint32_t parity) {
    uint32_t ok;
    asm volatile("{\n.reg .pred p;\nmbarrier.try_wait.parity.shared::cta.b64 p, [%1], %2;\nselp.u32 %0, 1, 0, p;\n}"
                 : "=r"(ok) : "r"(bar), "r"(parity) : "memory");
    return ok;
}
__device__ __forceinline__ bool mbar_test(uint32_t bar, uint32_t parity) {
    uint32_t ok;
    asm volatile("{\n.reg .pred p;\nmbarrier.test_wait.parity.shared::cta.b64 p, [%1], %2;\nselp.u32 %0, 1, 0, p;\n}"
                 : "=r"(ok) : "r"(bar), "r"(parity) : "memory");
    return ok;
}
__device__ __forceinline__ void mbar_wait(uint32_t bar, uint32_t parity) {
    asm volatile("{\n.reg .pred p, q;\n.reg .u32 n;\n"
                 "mbarrier.try_wait.parity.shared::cta.b64 p, [%0], %1;\n@p bra DONE;\nmov.u32 n, 0;\n"
                 "AGAIN:\nmbarrier.try_wait.parity.shared::cta.b64 p, [%0], %1;\nadd.u32 n, n, 1;\n"
                 "setp.lt.and.u32 q, n, 0x400000, !p;\n@q bra AGAIN;\nDONE:\n}"
                 ::"r"(bar), "r"(parity) : "memory");
}
__device__ __forceinline__ uint32_t mapa(uint32_t addr, uint32_t rank) {
    uint32_t r;
    asm("mapa.shared::cluster.u32 %0, %1, %2;" : "=r"(r) : "r"(addr), "r"(rank));
    return r;
}
__device__ __forceinline__ void fence_async_smem() { asm volatile("fence.proxy.async.shared::cta;" ::: "memory"); }
__device__ __forceinline__ void post_tile(uint32_t bar, uint32_t slot, uint32_t bytes, int value) {
    asm volatile("mbarrier.arrive.expect_tx.shared::cluster.b64 _, [%0], %1;" ::"r"(bar), "r"(bytes) : "memory");
    asm volatile("st.async.weak.shared::cluster.mbarrier::complete_tx::bytes.b32 [%0], %1, [%2];"
                 ::"r"(slot), "r"(value), "r"(bar) : "memory");
}
__device__ __forceinline__ void tma_load_w(uint32_t dst, const CUtensorMap* tm, int ch, uint32_t bar) {
    asm volatile("cp.async.bulk.tensor.3d.shared::cluster.global.mbarrier::complete_tx::bytes [%0], [%1, {%3, %4, %4}], [%2];"
                 ::"r"(dst), "l"(tm), "r"(bar), "r"(ch), "r"(0) : "memory");
}
__device__ __forceinline__ void tma_load_x(uint32_t dst, const CUtensorMap* tm, int tile, uint32_t bar) {
    asm volatile("cp.async.bulk.tensor.4d.shared::cluster.global.mbarrier::complete_tx::bytes"
                 " [%0], [%1, {%4, %4, %4, %3}], [%2];"
                 ::"r"(dst), "l"(tm), "r"(bar), "r"(tile * (TP / 8)), "r"(0) : "memory");
}
__device__ __forceinline__ void tma_load_x_multicast(uint32_t dst, const CUtensorMap* tm, int tile, uint32_t bar) {
    asm volatile("cp.async.bulk.tensor.4d.shared::cluster.global.mbarrier::complete_tx::bytes.multicast::cluster"
                 " [%0], [%1, {%4, %4, %4, %3}], [%2], %5;"
                 ::"r"(dst), "l"(tm), "r"(bar), "r"(tile * (TP / 8)), "r"(0), "h"((uint16_t)3) : "memory");
}
__device__ __forceinline__ void tma_store_out(const CUtensorMap* tm, uint32_t src, int slab, int tile) {
    asm volatile("cp.async.bulk.tensor.4d.global.shared::cta.bulk_group [%0, {%4, %4, %2, %3}], [%1];"
                 ::"l"(tm), "r"(src), "r"(slab), "r"(tile * (TP / 8)), "r"(0) : "memory");
    asm volatile("cp.async.bulk.commit_group;" ::: "memory");
}
__device__ __forceinline__ void l2_prefetch(const void* p, uint32_t bytes) {
    asm volatile("cp.async.bulk.prefetch.L2.global [%0], %1;" ::"l"(p), "r"(bytes) : "memory");
}

__device__ __forceinline__ void l2_prefetch_tile(const CUtensorMap* tm, int tile) {
    asm volatile("cp.async.bulk.prefetch.tensor.2d.L2.global.tile [%0, {%1, %2}];"
                 ::"l"(tm), "r"(0), "r"(tile * (STAGE_BYTES / 128)) : "memory");
}

__device__ __forceinline__ void wgmma_rs(float (&d)[16], const uint32_t (&a)[4], uint64_t desc, int scale_d) {
    asm volatile(
        "{\n.reg .pred p;\nsetp.ne.b32 p, %21, 0;\n"
        "wgmma.mma_async.sync.aligned.m64n32k16.f32.bf16.bf16 "
        "{%0,%1,%2,%3,%4,%5,%6,%7,%8,%9,%10,%11,%12,%13,%14,%15},"
        "{%16,%17,%18,%19}, %20, p, 1, 1, 0;\n}"
        : "+f"(d[0]), "+f"(d[1]), "+f"(d[2]), "+f"(d[3]), "+f"(d[4]), "+f"(d[5]), "+f"(d[6]), "+f"(d[7]),
          "+f"(d[8]), "+f"(d[9]), "+f"(d[10]), "+f"(d[11]), "+f"(d[12]), "+f"(d[13]), "+f"(d[14]), "+f"(d[15])
        : "r"(a[0]), "r"(a[1]), "r"(a[2]), "r"(a[3]), "l"(desc), "r"(scale_d));
}
template <bool HI>
__device__ __forceinline__ uint32_t cvt_add_bias(float lo, float hi, uint32_t bias2) {
    uint32_t r;
    if (HI) asm("{\n.reg .b32 t, b;\n.reg .b16 l, h;\ncvt.rn.bf16x2.f32 t, %2, %1;\nmov.b32 {l, h}, %3;\nmov.b32 b, {h, h};\n"
                "add.rn.bf16x2 %0, t, b;\n}" : "=r"(r) : "f"(lo), "f"(hi), "r"(bias2));
    else asm("{\n.reg .b32 t, b;\n.reg .b16 l, h;\ncvt.rn.bf16x2.f32 t, %2, %1;\nmov.b32 {l, h}, %3;\nmov.b32 b, {l, l};\n"
             "add.rn.bf16x2 %0, t, b;\n}" : "=r"(r) : "f"(lo), "f"(hi), "r"(bias2));
    return r;
}

__global__ void __cluster_dims__(2, 1, 1) __launch_bounds__(NTHREADS, 1)
conv1x1_kernel(const __nv_bfloat16* __restrict__ x, const __nv_bfloat16* __restrict__ w,
               const __nv_bfloat16* __restrict__ bias, int num_units,
               const __grid_constant__ CUtensorMap tm_x, const __grid_constant__ CUtensorMap tm_w,
               const __grid_constant__ CUtensorMap tm_o, const __grid_constant__ CUtensorMap tm_p) {
    extern __shared__ uint8_t smem_raw[];
    const uint32_t smem = (smem_u32(smem_raw) + 1023u) & ~1023u;
    const uint32_t bar_full   = smem + SMEM_BAR;
    const uint32_t bar_empty  = bar_full + 8 * STAGES;
    const uint32_t bar_ofull  = bar_empty + 8 * STAGES;
    const uint32_t bar_oempty = bar_ofull + 8 * NBUF;
    const uint32_t bar_w      = bar_oempty + 8 * NBUF;
    const uint32_t bar_wfree  = bar_w + 24;
    const uint32_t bar_wloc   = bar_wfree + 8;
    const uint32_t bar_spare  = bar_wloc + 8;
    const uint32_t progress   = bar_spare + 16;
    const uint32_t total_slot = progress + 4;
    const uint32_t dry_slot   = progress + 8;
    const uint32_t zero_slot  = progress + 12;
    const uint32_t tile_slot  = progress + 16;

    const int tid = threadIdx.x;
    const int wg  = tid >> 7;
    uint32_t rank;
    asm("mov.u32 %0, %%cluster_ctarank;" : "=r"(rank));
    const int cluster_id = blockIdx.x >> 1;
    const int nclusters  = gridDim.x >> 1;
    const int ntiles     = num_units * UNIT;

    asm volatile("setmaxnreg.dec.sync.aligned.u32 32;");

    uint32_t t_entry = 0;
    if (tid == 448) {
        if (blockIdx.x < 128) l2_prefetch(w + blockIdx.x * (C * C / 128), C * C * 2 / 128);
        l2_prefetch(x + (size_t)(cluster_id * (UNIT * TP) + rank * (TP / 2)) * C, STAGE_BYTES / 2);
        t_entry = now_ns();
        asm volatile("prefetch.tensormap [%0];" ::"l"(&tm_p) : "memory");
    }
    if (tid == 384) {
        asm volatile("prefetch.tensormap [%0];" ::"l"(&tm_w) : "memory");
        asm volatile("prefetch.tensormap [%0];" ::"l"(&tm_x) : "memory");
        for (int g = 0; g < 3; g++) mbar_init(bar_w + 8 * g, 1);
        for (int s = 0; s < NLOCAL; s++) mbar_init(bar_full + 8 * s, 1);
        asm volatile("fence.mbarrier_init.release.cluster;" ::: "memory");
        fence_async_smem();
        for (int g = 0; g < 3; g++) {
            mbar_expect_tx(bar_w + 8 * g, SLAB_BYTES);
            tma_load_w(smem + SMEM_W + g * SLAB_BYTES, &tm_w, rank * 192 + g * 64, bar_w + 8 * g);
        }
        for (int s = 0; s < NLOCAL; s++) {
            sts(tile_slot + 4 * s, cluster_id * UNIT + s);
            mbar_expect_tx(bar_full + 8 * s, STAGE_BYTES);
            tma_load_x(smem + s * STAGE_BYTES, &tm_x, cluster_id * UNIT + s, bar_full + 8 * s);
        }
    }
    if (tid == 416) {
        for (int s = NLOCAL; s < STAGES; s++) mbar_init(bar_full + 8 * s, 1);
        for (int s = 0; s < STAGES; s++) mbar_init(bar_empty + 8 * s, 24);
        for (int s = 0; s < NBUF; s++) {
            mbar_init(bar_ofull + 8 * s, 12);
            mbar_init(bar_oempty + 8 * s, 1);
        }
        mbar_init(bar_wfree, 24);
        mbar_init(bar_wloc, 12);
        mbar_init(bar_spare, 1);
        mbar_init(bar_spare + 8, 1);
        sts(progress, 0);
        sts(total_slot, 0);
        sts(dry_slot, 0);
        sts(zero_slot, 0);
        asm volatile("fence.mbarrier_init.release.cluster;" ::: "memory");
        fence_async_smem();
        asm volatile("prefetch.tensormap [%0];" ::"l"(&tm_o) : "memory");
    }
    __syncwarp();
    asm volatile("barrier.cluster.arrive.relaxed.aligned;" ::: "memory");

    if (wg == 3) {
        if (tid == 448) {
            while (now_ns() - t_entry < (uint32_t)X1_T) {}
            l2_prefetch(x + ((size_t)cluster_id * (UNIT * TP) + TP + rank * (TP / 2)) * C, STAGE_BYTES / 2);
        }
        __syncwarp();
        asm volatile("barrier.cluster.wait.aligned;" ::: "memory");
        if (tid == 384 && rank == 0) {
            const uint32_t peer = mapa(smem, 1) - smem;
            const int shallow = max(ntiles - SHALLOW * nclusters, STAGES * nclusters);
            int s = NLOCAL, n = 0;
            uint32_t ph = 1;
            int unit = cluster_id;
            for (int u = 0; unit < num_units; u++) {
                const bool late = unit >= num_units - 3 * nclusters;
                const unsigned long long t_fetch = late ? now_ns64() : 0;
                int next = unit - (NSTATIC - 1) * nclusters;
                if (u >= NSTATIC - 1) next = (int)atomicInc(&g_sched, (unsigned)(num_units - (NSTATIC - 1) * nclusters - 1));
#pragma unroll 1
                for (int h = 0; h < UNIT; h++, n++) {
                    if (n < NLOCAL) continue;
                    const int tile = unit * UNIT + h;
                    if (n == FREE_STAGES) mbar_wait(bar_wfree, 0);
                    mbar_wait(bar_empty + 8 * s, ph);
                    if (tile >= shallow) mbar_wait(bar_empty + 8 * ((s + 1) & 3), s == 3 ? ph ^ 1 : ph);
                    const uint32_t bar = bar_full + 8 * s;
                    tma_load_x_multicast(smem + s * STAGE_BYTES, &tm_x, tile, bar);
                    post_tile(bar, tile_slot + 4 * (n & 31), STAGE_BYTES + 4, tile);
                    post_tile(bar + peer, tile_slot + 4 * (n & 31) + peer, STAGE_BYTES + 4, tile);
                    sts_cluster(progress + peer, tile);
                    if (++s == STAGES) { s = 0; ph ^= 1; }
                    if (late && h == 0) {
                        asm volatile("" : "+r"(next)::"memory");
                        const int succ = next + NSTATIC * nclusters;
                        if (succ >= num_units) {
                            sts(total_slot, n + UNIT);
                            sts_cluster(total_slot + peer, n + UNIT);
                        }
                        if (succ == num_units - 1)
                            asm volatile("st.relaxed.gpu.global.b64 [%0], %1;" ::"l"(&g_dry), "l"(t_fetch) : "memory");
                    }
                }
                asm volatile("" : "+r"(next)::"memory");
                unit = next + NSTATIC * nclusters;
            }
            sts(total_slot, n);
            sts_cluster(total_slot + peer, n);
            sts_cluster(progress + peer, 0x7fffffff);
            mbar_wait(bar_empty + 8 * s, ph);
            post_tile(bar_full + 8 * s, tile_slot + 4 * (n & 31), 4, -1);
            post_tile(bar_full + 8 * s + peer, tile_slot + 4 * (n & 31) + peer, 4, -1);
#pragma unroll 1
            for (int e = 1; e < STAGES; e++) {
                if (++s == STAGES) { s = 0; ph ^= 1; }
                mbar_wait(bar_empty + 8 * s, ph);
            }
        } else if (tid == 448 && rank == 1) {
            auto wait_loader = [&](int tile, uint32_t unless) {
                while (lds(progress) < tile && lds(unless) == 0 && now_ns() - t_entry < 1000000000u) __nanosleep(64);
            };
            const int slope = (RA_LEAD - RA_MIN) * 256 / (RA_END - RA_FADE);
            int lead = RA_LEAD * 256;
            uint32_t due = RA_T0;
#pragma unroll 1
            for (int j = NLOCAL; j * nclusters < ntiles; j++, due += RA_DT) {
                const int t = j < NSTATIC * UNIT ? (cluster_id + (j / UNIT) * nclusters) * UNIT + j % UNIT
                                                 : j * nclusters + cluster_id;
                if (j >= RA_FADE && j < RA_END) lead -= slope;
                wait_loader(t - (lead * nclusters >> 10), dry_slot);
                while (now_ns() - t_entry < due) {}
                if (t < ntiles) l2_prefetch_tile(&tm_p, t);
            }
            wait_loader(0x7fffffff, zero_slot);
        } else if (tid == 384 || tid == 448) {
            const unsigned long long t_start = now_ns64();
            for (uint32_t it = 0; it < (1u << 22); it++) {
                unsigned long long v;
                asm volatile("ld.relaxed.gpu.global.b64 %0, [%1];" : "=l"(v) : "l"(&g_dry) : "memory");
                if (v > t_start) { sts(dry_slot, (uint32_t)v | 1); break; }
                if (lds(dry_slot)) break;
                __nanosleep(200);
            }
        } else if ((tid & 63) == 32) {
            uint32_t base = smem;
            asm volatile("" : "+r"(base));
            const uint32_t ofull = base + (bar_ofull - smem), otile = base + (tile_slot - smem);
            const uint32_t total_at = base + (total_slot - smem);
            int k = (tid >> 6) & 1;
            auto wait_filled = [&](int j) -> bool {
                const uint32_t lap = (uint32_t)j / NBUF, bar = ofull + 8 * (j - lap * NBUF);
                for (uint32_t it = 0; it < (1u << 22); it++) {
                    if (mbar_try(bar, lap & 1)) return true;
                    const int total = lds(total_at);
                    if (total != 0 && j >= total) break;
                }
                return false;
            };
            auto test_filled = [&](int j) -> bool {
                const uint32_t lap = (uint32_t)j / NBUF;
                return mbar_test(ofull + 8 * (j - lap * NBUF), lap & 1);
            };
            const int skew = cluster_id & 1;
            auto trigger = [&]() -> int { return k + min(max(0, RAMP_0 + (k + skew) * RAMP_Q) >> 4, NBUF - 1); };
            auto store = [&]() -> int {
                const int tile = lds(otile + 4 * (k & 31));
                const uint32_t slot = (uint32_t)k % NBUF;
                tma_store_out(&tm_o, base + SMEM_OUT + slot * OUT_BYTES, rank * 3, tile);
                asm volatile("cp.async.bulk.wait_group.read 0;" ::: "memory");
                mbar_arrive(ofull + 8 * (NBUF + slot));
                k += 2;
                return tile;
            };
            const int near_end = ntiles - (KREG + 2 * NBUF) * nclusters;
            while (wait_filled(trigger()))
                if (store() >= near_end) break;
            uint32_t t_dry = 0, due = 0;
            for (uint32_t it = 0; it < (1u << 22); it++) {
                int total = lds(total_at);
                const int m = trigger();
                if ((total == 0 || m < total) && test_filled(m)) { store(); continue; }
                t_dry = lds(base + (dry_slot - smem));
                if (t_dry) {
                    if (total == 0) total = m + KREG + STAGES + DRAIN_PRE;
                    due = t_dry + max(DRAIN_T0, DRAIN_END - (total - k) * DRAIN_DT);
                    if ((int)(now_ns() - due) >= 0) break;
                } else if (total != 0 && total <= m + 1 && test_filled(total - 1)) {
                    break;
                }
            }
            if (!t_dry) {
                due = now_ns();
                t_dry = (due - DRAIN_END) | 1;
                sts(base + (dry_slot - smem), t_dry);
            }
            uint32_t prev = base + (bar_spare - smem) + 8 * (k & 1);
            while (true) {
                const int total = lds(total_at);
                if (total != 0) {
                    if (k >= total) break;
                    due = t_dry + DRAIN_END - (total - k) * DRAIN_DT;
                }
                if (!wait_filled(k)) break;
                const int tile = lds(otile + 4 * (k & 31));
                const uint32_t slot = (uint32_t)k % NBUF;
                while ((int)(now_ns() - due) < 0) {}
                tma_store_out(&tm_o, base + SMEM_OUT + slot * OUT_BYTES, rank * 3, tile);
                asm volatile("cp.async.bulk.wait_group.read 1;" ::: "memory");
                mbar_arrive(prev);
                prev = ofull + 8 * (NBUF + slot);
                k += 2;
                due += 2 * DRAIN_DT;
            }
            asm volatile("cp.async.bulk.wait_group.read 0;" ::: "memory");
        }
    } else {
        asm volatile("setmaxnreg.inc.sync.aligned.u32 160;");
        const int lane = tid & 31;
        const int warp = (tid >> 5) & 3;
        if (wg == 2) asm volatile("bar.arrive 8, 256;" ::: "memory");

        uint32_t bias2;
        {
            const unsigned short* bp =
                reinterpret_cast<const unsigned short*>(bias) + rank * 192 + wg * 64 + warp * 16 + (lane >> 2);
            const uint32_t b0 = bp[0], b1 = bp[8];
            bias2 = b0 | (b1 << 16);
        }
        const uint32_t swz = (uint32_t)(((warp * 2 + ((lane >> 3) & 1)) ^ (lane & 7)) << 4);
        const uint32_t lead = mapa(smem, 0) - smem;

        uint32_t a[24][4];
        asm volatile("barrier.cluster.wait.aligned;" ::: "memory");
        mbar_wait(bar_w + 8 * wg, 0);
        {
            const uint32_t base = smem + SMEM_W + wg * SLAB_BYTES + ((lane >> 4) * 8 + (lane & 7)) * 128 + swz;
#pragma unroll
            for (int ks = 0; ks < 24; ks++)
                asm volatile("ldmatrix.sync.aligned.m8n8.x4.trans.shared.b16 {%0,%1,%2,%3}, [%4];"
                             : "=r"(a[ks][0]), "=r"(a[ks][1]), "=r"(a[ks][2]), "=r"(a[ks][3])
                             : "r"(base + ks * 2048) : "memory");
        }
        fence_async_smem();
        __syncwarp();
        if (lane == 0) {
            mbar_arrive_cluster(bar_wfree + lead);
            mbar_arrive(bar_wloc);
        }

        uint32_t st_base = smem + SMEM_OUT + wg * 1024 + (lane >> 4) * 3072 + (lane & 7) * 128 + swz;
        const int wgu = __shfl_sync(0xffffffffu, wg, 0);
        asm volatile("" : "+r"(st_base), "+r"(bias2));
        const uint64_t desc0 = (uint64_t)((smem & 0x3FFFF) >> 4) | (1ull << 16) | ((6144ull >> 4) << 32) | (1ull << 62);

        int s = 0, ob = 0, i = 0;
        uint32_t ph = 0, oph = 1;
        float d[16];
        uint32_t q[KREG][8];
        auto compute = [&]() -> bool {
            mbar_wait(bar_full + 8 * s, ph);
            if (lds(tile_slot + 4 * (i & 31)) < 0) return false;
            const uint64_t desc = desc0 + (uint64_t)(s * (STAGE_BYTES >> 4));
            asm volatile("bar.sync %0, 256;" ::"r"(8 + wgu) : "memory");
            asm volatile("wgmma.fence.sync.aligned;" ::: "memory");
#pragma unroll
            for (int ks = 0; ks < 24; ks++) {
                wgmma_rs(d, a[ks], desc + (uint64_t)(((ks >> 2) * 1024 + (ks & 3) * 32) >> 4), ks != 0);
                if (ks == HANDOVER - 1) asm volatile("bar.arrive %0, 256;" ::"r"(wgu == 2 ? 8 : 9 + wgu) : "memory");
            }
            asm volatile("wgmma.commit_group.sync.aligned;" ::: "memory");
            asm volatile("wgmma.wait_group.sync.aligned 0;" ::: "memory");
#pragma unroll
            for (int j = 0; j < 16; j++) asm volatile("" : "+f"(d[j])::"memory");
            if (lane == 0) mbar_arrive_cluster(bar_empty + 8 * s + lead);
            if (++s == STAGES) { s = 0; ph ^= 1; }
            return true;
        };
        auto pack = [&](uint32_t (&p)[8]) {
#pragma unroll
            for (int j = 0; j < 8; j += 2) {
                p[j]     = cvt_add_bias<false>(d[2 * j], d[2 * j + 1], bias2);
                p[j + 1] = cvt_add_bias<true>(d[2 * j + 2], d[2 * j + 3], bias2);
            }
        };
        auto put = [&](uint32_t st, const uint32_t (&p)[8]) {
#pragma unroll
            for (int j = 0; j < 2; j++)
                asm volatile("stmatrix.sync.aligned.m8n8.x4.trans.shared.b16 [%0], {%1,%2,%3,%4};"
                             ::"r"(st + j * 6144), "r"(p[4 * j]), "r"(p[4 * j + 1]), "r"(p[4 * j + 2]), "r"(p[4 * j + 3])
                             : "memory");
        };
        auto acquire = [&]() -> uint32_t {
            mbar_wait(bar_oempty + 8 * ob, oph);
            return st_base + ob * OUT_BYTES;
        };
        auto publish = [&]() {
            fence_async_smem();
            __syncwarp();
            if (lane == 0) mbar_arrive(bar_ofull + 8 * ob);
            if (++ob == NBUF) { ob = 0; oph ^= 1; }
        };

        const int kstart = KSTART - cluster_id % KRAMP;
        int held = 0, h = 0;
        bool more = true;
#pragma unroll 1
        for (; i < kstart; i++) {
            more = compute();
            if (!more) break;
            pack(q[0]);
            if (i == 0) mbar_wait(bar_wloc, 0);
            put(acquire(), q[0]);
            publish();
        }
        if (more) {
            int kstep = kstart;
#pragma unroll 1
            for (; compute(); i++) {
                if (h == 0 && i >= kstep) {
#pragma unroll
                    for (int k = 0; k < KREG; k++)
                        if (held == k) pack(q[k]);
                    kstep = ++held == KREG ? 0x7fffffff : kstep + KRAMP;
                    continue;
                }
                const uint32_t st = acquire();
#pragma unroll
                for (int k = 0; k < KREG; k++)
                    if (h == k) { put(st, q[k]); pack(q[k]); }
                publish();
                if (++h == held) h = 0;
            }
#pragma unroll 1
            for (int left = held; left > 0; left--) {
                const uint32_t st = acquire();
#pragma unroll
                for (int k = 0; k < KREG; k++)
                    if (h == k) put(st, q[k]);
                publish();
                if (++h == held) h = 0;
            }
        }
        if (wg == 0) asm volatile("bar.sync 8, 256;" ::: "memory");
    }
}

typedef CUresult (*EncodeTiledFn)(CUtensorMap*, CUtensorMapDataType, cuuint32_t, void*, const cuuint64_t*,
                                  const cuuint64_t*, const cuuint32_t*, const cuuint32_t*, CUtensorMapInterleave,
                                  CUtensorMapSwizzle, CUtensorMapL2promotion, CUtensorMapFloatOOBfill);

void encode_map(EncodeTiledFn fn, CUtensorMap* tm, const void* ptr, int rank, const cuuint64_t* dims,
                const cuuint64_t* strides, const cuuint32_t* box) {
    const cuuint32_t estr[4] = {1, 1, 1, 1};
    fn(tm, CU_TENSOR_MAP_DATA_TYPE_BFLOAT16, rank, const_cast<void*>(ptr), dims, strides, box, estr,
       CU_TENSOR_MAP_INTERLEAVE_NONE, CU_TENSOR_MAP_SWIZZLE_128B, CU_TENSOR_MAP_L2_PROMOTION_L2_128B,
       CU_TENSOR_MAP_FLOAT_OOB_FILL_NONE);
}

}

extern "C" void kernel_launch(void* const* d_in, const int* in_sizes, int n_in, void* d_out, int out_size) {
    const __nv_bfloat16* x = (const __nv_bfloat16*)d_in[0];
    const __nv_bfloat16* w = (const __nv_bfloat16*)d_in[1];
    const __nv_bfloat16* b = (const __nv_bfloat16*)d_in[2];
    const int pixels = in_sizes[0] / C;

    static EncodeTiledFn encode = nullptr;
    static int max_clusters = 0;
    if (!encode) {
        void* fn = nullptr;
        cudaDriverEntryPointQueryResult qr;
        cudaGetDriverEntryPoint("cuTensorMapEncodeTiled", &fn, cudaEnableDefault, &qr);
        encode = (EncodeTiledFn)fn;
        cudaFuncSetAttribute(conv1x1_kernel, cudaFuncAttributeMaxDynamicSharedMemorySize, SMEM_TOTAL);
        cudaLaunchConfig_t cfg = {};
        cfg.gridDim = dim3(2, 1, 1);
        cfg.blockDim = dim3(NTHREADS, 1, 1);
        cfg.dynamicSmemBytes = SMEM_TOTAL;
        cudaLaunchAttribute at[1];
        at[0].id = cudaLaunchAttributeClusterDimension;
        at[0].val.clusterDim.x = 2; at[0].val.clusterDim.y = 1; at[0].val.clusterDim.z = 1;
        cfg.attrs = at; cfg.numAttrs = 1;
        if (cudaOccupancyMaxActiveClusters(&max_clusters, conv1x1_kernel, &cfg) != cudaSuccess || max_clusters <= 0) {
            (void)cudaGetLastError();
            int dev = 0, sms = 0;
            cudaGetDevice(&dev);
            cudaDeviceGetAttribute(&sms, cudaDevAttrMultiProcessorCount, dev);
            max_clusters = sms / 2;
        }
    }
    CUtensorMap tm_x, tm_w, tm_o, tm_p;
    {
        const cuuint64_t dims[4]    = {64, 8, 6, (cuuint64_t)(pixels / 8)};
        const cuuint64_t strides[3] = {C * 2, 128, C * 2 * 8};
        const cuuint32_t box_x[4]   = {64, 8, 6, TP / 8};
        const cuuint32_t box_o[4]   = {64, 8, 3, TP / 8};
        encode_map(encode, &tm_x, x, 4, dims, strides, box_x);
        encode_map(encode, &tm_o, d_out, 4, dims, strides, box_o);
        const cuuint64_t pdims[2]    = {64, (cuuint64_t)pixels * 6};
        const cuuint64_t pstrides[1] = {128};
        const cuuint32_t pbox[2]     = {64, STAGE_BYTES / 128};
        encode_map(encode, &tm_p, x, 2, pdims, pstrides, pbox);
        const cuuint64_t wdims[3]    = {C, 192, 2};
        const cuuint64_t wstrides[2] = {C * 2, C * 2 * 192};
        const cuuint32_t wbox[3]     = {64, 192, 2};
        encode_map(encode, &tm_w, w, 3, wdims, wstrides, wbox);
    }
    const int num_units = pixels / (TP * UNIT);
    const int nclusters = max_clusters * NSTATIC <= num_units ? max_clusters : num_units / NSTATIC;
    conv1x1_kernel<<<2 * nclusters, NTHREADS, SMEM_TOTAL, cudaStreamPerThread>>>(x, w, b, num_units, tm_x, tm_w, tm_o, tm_p);
}
```

```cpp
#include <cuda_runtime.h>
#include <cuda_bf16.h>
#include <cuda.h>
#include <stdint.h>

#define TUNE(name, value) constexpr int name = value
TUNE(RAMP_Q, 11);
TUNE(RAMP_0, -8);
TUNE(KSTART, 26);
TUNE(KRAMP, 4);
TUNE(X1_T, 225);
TUNE(RA_T0, 900);
TUNE(RA_DT, 468);
TUNE(RA_LEAD, 40);
TUNE(RA_FADE, 7);
TUNE(RA_END, 63);
TUNE(RA_MIN, 8);
TUNE(SHALLOW, 13);
TUNE(DRAIN_T0, 600);
TUNE(DRAIN_END, 11125);
TUNE(DRAIN_DT, 470);
TUNE(DRAIN_PRE, 2);

namespace {

constexpr int C           = 384;
constexpr int TP          = 32;
constexpr int UNIT        = 2;
constexpr int NSTATIC     = 4;
constexpr int KREG        = 5;
constexpr int HANDOVER    = 18;
constexpr int STAGES      = 4;
constexpr int NBUF        = 10;
constexpr int NLOCAL      = 2;
constexpr int STAGE_BYTES = TP * C * 2;
constexpr int OUT_BYTES   = TP * 192 * 2;
constexpr int SLAB_BYTES  = C * 64 * 2;
constexpr int SMEM_OUT    = STAGES * STAGE_BYTES;
constexpr int SMEM_BAR    = SMEM_OUT + NBUF * OUT_BYTES;
constexpr int SMEM_TOTAL  = SMEM_BAR + 512 + 1024;
constexpr int NTHREADS    = 512;
constexpr int SMEM_W      = SMEM_BAR - 3 * SLAB_BYTES;
constexpr int FREE_STAGES = SMEM_W / STAGE_BYTES;
static_assert(SMEM_W % 1024 == 0 && NLOCAL <= FREE_STAGES && FREE_STAGES < NSTATIC * UNIT, "layout");
static_assert(STAGES == 4 && NSTATIC * UNIT >= STAGES, "the shallow mode of the loader assumes four stages");
static_assert(SMEM_TOTAL <= 232448, "too much shared memory");

__device__ unsigned int g_sched;
__device__ unsigned long long g_dry;
__device__ unsigned int g_seen;

__device__ __forceinline__ uint32_t smem_u32(const void* p) { return (uint32_t)__cvta_generic_to_shared(p); }
__device__ __forceinline__ uint32_t now_ns() {
    uint32_t t;
    asm volatile("mov.u32 %0, %%globaltimer_lo;" : "=r"(t));
    return t;
}
__device__ __forceinline__ unsigned long long now_ns64() {
    unsigned long long t;
    asm volatile("mov.u64 %0, %%globaltimer;" : "=l"(t));
    return t;
}
__device__ __forceinline__ int lds(uint32_t addr) {
    int v;
    asm volatile("ld.volatile.shared.b32 %0, [%1];" : "=r"(v) : "r"(addr) : "memory");
    return v;
}
__device__ __forceinline__ void sts(uint32_t addr, int v) {
    asm volatile("st.volatile.shared.b32 [%0], %1;" ::"r"(addr), "r"(v) : "memory");
}
__device__ __forceinline__ void sts_cluster(uint32_t cluster_addr, int v) {
    asm volatile("st.volatile.shared::cluster.b32 [%0], %1;" ::"r"(cluster_addr), "r"(v) : "memory");
}
__device__ __forceinline__ void mbar_init(uint32_t bar, uint32_t count) {
    asm volatile("mbarrier.init.shared::cta.b64 [%0], %1;" ::"r"(bar), "r"(count) : "memory");
}
__device__ __forceinline__ void mbar_expect_tx(uint32_t bar, uint32_t bytes) {
    asm volatile("mbarrier.arrive.expect_tx.shared::cta.b64 _, [%0], %1;" ::"r"(bar), "r"(bytes) : "memory");
}
__device__ __forceinline__ void mbar_arrive(uint32_t bar) {
    asm volatile("mbarrier.arrive.shared::cta.b64 _, [%0];" ::"r"(bar) : "memory");
}
__device__ __forceinline__ void mbar_arrive_cluster(uint32_t cluster_addr) {
    asm volatile("mbarrier.arrive.shared::cluster.b64 _, [%0];" ::"r"(cluster_addr) : "memory");
}
__device__ __forceinline__ bool mbar_try(uint32_t bar, uint32_t parity) {
    uint32_t ok;
    asm volatile("{\n.reg .pred p;\nmbarrier.try_wait.parity.shared::cta.b64 p, [%1], %2;\nselp.u32 %0, 1, 0, p;\n}"
                 : "=r"(ok) : "r"(bar), "r"(parity) : "memory");
    return ok;
}
__device__ __forceinline__ bool mbar_test(uint32_t bar, uint32_t parity) {
    uint32_t ok;
    asm volatile("{\n.reg .pred p;\nmbarrier.test_wait.parity.shared::cta.b64 p, [%1], %2;\nselp.u32 %0, 1, 0, p;\n}"
                 : "=r"(ok) : "r"(bar), "r"(parity) : "memory");
    return ok;
}
__device__ __forceinline__ void mbar_wait(uint32_t bar, uint32_t parity) {
    asm volatile("{\n.reg .pred p, q;\n.reg .u32 n;\n"
                 "mbarrier.try_wait.parity.shared::cta.b64 p, [%0], %1;\n@p bra DONE;\nmov.u32 n, 0;\n"
                 "AGAIN:\nmbarrier.try_wait.parity.shared::cta.b64 p, [%0], %1;\nadd.u32 n, n, 1;\n"
                 "setp.lt.and.u32 q, n, 0x400000, !p;\n@q bra AGAIN;\nDONE:\n}"
                 ::"r"(bar), "r"(parity) : "memory");
}
__device__ __forceinline__ uint32_t mapa(uint32_t addr, uint32_t rank) {
    uint32_t r;
    asm("mapa.shared::cluster.u32 %0, %1, %2;" : "=r"(r) : "r"(addr), "r"(rank));
    return r;
}
__device__ __forceinline__ void fence_async_smem() { asm volatile("fence.proxy.async.shared::cta;" ::: "memory"); }
__device__ __forceinline__ void post_tile(uint32_t bar, uint32_t slot, uint32_t bytes, int value) {
    asm volatile("mbarrier.arrive.expect_tx.shared::cluster.b64 _, [%0], %1;" ::"r"(bar), "r"(bytes) : "memory");
    asm volatile("st.async.weak.shared::cluster.mbarrier::complete_tx::bytes.b32 [%0], %1, [%2];"
                 ::"r"(slot), "r"(value), "r"(bar) : "memory");
}
__device__ __forceinline__ void tma_load_w(uint32_t dst, const CUtensorMap* tm, int ch, uint32_t bar) {
    asm volatile("cp.async.bulk.tensor.3d.shared::cluster.global.mbarrier::complete_tx::bytes [%0], [%1, {%3, %4, %4}], [%2];"
                 ::"r"(dst), "l"(tm), "r"(bar), "r"(ch), "r"(0) : "memory");
}
__device__ __forceinline__ void tma_load_x(uint32_t dst, const CUtensorMap* tm, int tile, uint32_t bar) {
    asm volatile("cp.async.bulk.tensor.4d.shared::cluster.global.mbarrier::complete_tx::bytes"
                 " [%0], [%1, {%4, %4, %4, %3}], [%2];"
                 ::"r"(dst), "l"(tm), "r"(bar), "r"(tile * (TP / 8)), "r"(0) : "memory");
}
__device__ __forceinline__ void tma_load_x_multicast(uint32_t dst, const CUtensorMap* tm, int tile, uint32_t bar) {
    asm volatile("cp.async.bulk.tensor.4d.shared::cluster.global.mbarrier::complete_tx::bytes.multicast::cluster"
                 " [%0], [%1, {%4, %4, %4, %3}], [%2], %5;"
                 ::"r"(dst), "l"(tm), "r"(bar), "r"(tile * (TP / 8)), "r"(0), "h"((uint16_t)3) : "memory");
}
__device__ __forceinline__ void tma_store_out(const CUtensorMap* tm, uint32_t src, int slab, int tile) {
    asm volatile("cp.async.bulk.tensor.4d.global.shared::cta.bulk_group [%0, {%4, %4, %2, %3}], [%1];"
                 ::"l"(tm), "r"(src), "r"(slab), "r"(tile * (TP / 8)), "r"(0) : "memory");
    asm volatile("cp.async.bulk.commit_group;" ::: "memory");
}
__device__ __forceinline__ void l2_prefetch(const void* p, uint32_t bytes) {
    asm volatile("cp.async.bulk.prefetch.L2.global [%0], %1;" ::"l"(p), "r"(bytes) : "memory");
}

__device__ __forceinline__ void l2_prefetch_tile(const CUtensorMap* tm, int tile) {
    asm volatile("cp.async.bulk.prefetch.tensor.2d.L2.global.tile [%0, {%1, %2}];"
                 ::"l"(tm), "r"(0), "r"(tile * (STAGE_BYTES / 128)) : "memory");
}

__device__ __forceinline__ void wgmma_rs(float (&d)[16], const uint32_t (&a)[4], uint64_t desc, int scale_d) {
    asm volatile(
        "{\n.reg .pred p;\nsetp.ne.b32 p, %21, 0;\n"
        "wgmma.mma_async.sync.aligned.m64n32k16.f32.bf16.bf16 "
        "{%0,%1,%2,%3,%4,%5,%6,%7,%8,%9,%10,%11,%12,%13,%14,%15},"
        "{%16,%17,%18,%19}, %20, p, 1, 1, 0;\n}"
        : "+f"(d[0]), "+f"(d[1]), "+f"(d[2]), "+f"(d[3]), "+f"(d[4]), "+f"(d[5]), "+f"(d[6]), "+f"(d[7]),
          "+f"(d[8]), "+f"(d[9]), "+f"(d[10]), "+f"(d[11]), "+f"(d[12]), "+f"(d[13]), "+f"(d[14]), "+f"(d[15])
        : "r"(a[0]), "r"(a[1]), "r"(a[2]), "r"(a[3]), "l"(desc), "r"(scale_d));
}
template <bool HI>
__device__ __forceinline__ uint32_t cvt_add_bias(float lo, float hi, uint32_t bias2) {
    uint32_t r;
    if (HI) asm("{\n.reg .b32 t, b;\n.reg .b16 l, h;\ncvt.rn.bf16x2.f32 t, %2, %1;\nmov.b32 {l, h}, %3;\nmov.b32 b, {h, h};\n"
                "add.rn.bf16x2 %0, t, b;\n}" : "=r"(r) : "f"(lo), "f"(hi), "r"(bias2));
    else asm("{\n.reg .b32 t, b;\n.reg .b16 l, h;\ncvt.rn.bf16x2.f32 t, %2, %1;\nmov.b32 {l, h}, %3;\nmov.b32 b, {l, l};\n"
             "add.rn.bf16x2 %0, t, b;\n}" : "=r"(r) : "f"(lo), "f"(hi), "r"(bias2));
    return r;
}

__global__ void __cluster_dims__(2, 1, 1) __launch_bounds__(NTHREADS, 1)
conv1x1_kernel(const __nv_bfloat16* __restrict__ x, const __nv_bfloat16* __restrict__ w,
               const __nv_bfloat16* __restrict__ bias, int num_units,
               const __grid_constant__ CUtensorMap tm_x, const __grid_constant__ CUtensorMap tm_w,
               const __grid_constant__ CUtensorMap tm_o, const __grid_constant__ CUtensorMap tm_p) {
    extern __shared__ uint8_t smem_raw[];
    const uint32_t smem = (smem_u32(smem_raw) + 1023u) & ~1023u;
    const uint32_t bar_full   = smem + SMEM_BAR;
    const uint32_t bar_empty  = bar_full + 8 * STAGES;
    const uint32_t bar_ofull  = bar_empty + 8 * STAGES;
    const uint32_t bar_oempty = bar_ofull + 8 * NBUF;
    const uint32_t bar_w      = bar_oempty + 8 * NBUF;
    const uint32_t bar_wfree  = bar_w + 24;
    const uint32_t bar_wloc   = bar_wfree + 8;
    const uint32_t bar_spare  = bar_wloc + 8;
    const uint32_t progress   = bar_spare + 16;
    const uint32_t total_slot = progress + 4;
    const uint32_t dry_slot   = progress + 8;
    const uint32_t zero_slot  = progress + 12;
    const uint32_t tile_slot  = progress + 16;

    const int tid = threadIdx.x;
    const int wg  = tid >> 7;
    uint32_t rank;
    asm("mov.u32 %0, %%cluster_ctarank;" : "=r"(rank));
    const int cluster_id = blockIdx.x >> 1;
    const int nclusters  = gridDim.x >> 1;
    const int ntiles     = num_units * UNIT;
    auto even_tile = [&](int j) { return (cluster_id + j / UNIT * nclusters) * UNIT + j % UNIT; };

    asm volatile("setmaxnreg.dec.sync.aligned.u32 32;");

    uint32_t t_entry = 0;
    if (tid == 448) {
        if (blockIdx.x < 128) l2_prefetch(w + blockIdx.x * (C * C / 128), C * C * 2 / 128);
        l2_prefetch(x + (size_t)(even_tile(0) * TP + rank * (TP / 2)) * C, STAGE_BYTES / 2);
        t_entry = now_ns();
        asm volatile("prefetch.tensormap [%0];" ::"l"(&tm_p) : "memory");
    }
    if (tid == 384) {
        asm volatile("prefetch.tensormap [%0];" ::"l"(&tm_w) : "memory");
        asm volatile("prefetch.tensormap [%0];" ::"l"(&tm_x) : "memory");
        for (int g = 0; g < 3; g++) mbar_init(bar_w + 8 * g, 1);
        for (int s = 0; s < NLOCAL; s++) mbar_init(bar_full + 8 * s, 1);
        asm volatile("fence.mbarrier_init.release.cluster;" ::: "memory");
        fence_async_smem();
        for (int g = 0; g < 3; g++) {
            mbar_expect_tx(bar_w + 8 * g, SLAB_BYTES);
            tma_load_w(smem + SMEM_W + g * SLAB_BYTES, &tm_w, rank * 192 + g * 64, bar_w + 8 * g);
        }
        for (int s = 0; s < NLOCAL; s++) {
            sts(tile_slot + 4 * s, even_tile(s));
            mbar_expect_tx(bar_full + 8 * s, STAGE_BYTES);
            tma_load_x(smem + s * STAGE_BYTES, &tm_x, even_tile(s), bar_full + 8 * s);
        }
    }
    if (tid == 416) {
        for (int s = NLOCAL; s < STAGES; s++) mbar_init(bar_full + 8 * s, 1);
        for (int s = 0; s < STAGES; s++) mbar_init(bar_empty + 8 * s, 24);
        for (int s = 0; s < NBUF; s++) {
            mbar_init(bar_ofull + 8 * s, 12);
            mbar_init(bar_oempty + 8 * s, 1);
        }
        mbar_init(bar_wfree, 24);
        mbar_init(bar_wloc, 12);
        mbar_init(bar_spare, 1);
        mbar_init(bar_spare + 8, 1);
        sts(progress, 0);
        sts(total_slot, 0);
        sts(dry_slot, 0);
        sts(zero_slot, 0);
        asm volatile("fence.mbarrier_init.release.cluster;" ::: "memory");
        fence_async_smem();
        asm volatile("prefetch.tensormap [%0];" ::"l"(&tm_o) : "memory");
    }
    __syncwarp();
    asm volatile("barrier.cluster.arrive.relaxed.aligned;" ::: "memory");

    if (wg == 3) {
        if (tid == 448) {
            while (now_ns() - t_entry < (uint32_t)X1_T) {}
            l2_prefetch(x + (size_t)(even_tile(1) * TP + rank * (TP / 2)) * C, STAGE_BYTES / 2);
        }
        __syncwarp();
        asm volatile("barrier.cluster.wait.aligned;" ::: "memory");
        if (tid == 384 && rank == 0) {
            const uint32_t peer = mapa(smem, 1) - smem;
            const int shallow = max(ntiles - SHALLOW * nclusters, NSTATIC * UNIT * nclusters);
            int s = NLOCAL, n = 0;
            uint32_t ph = 1;
            int unit = cluster_id;
            for (int u = 0; unit < num_units; u++) {
                const bool late = unit * UNIT >= ntiles - 6 * nclusters;
                const unsigned long long t_fetch = late ? now_ns64() : 0;
                int next = unit - (NSTATIC - 1) * nclusters;
                if (u >= NSTATIC - 1) next = (int)atomicInc(&g_sched, (unsigned)(num_units - (NSTATIC - 1) * nclusters - 1));
#pragma unroll 1
                for (int h = 0; h < UNIT; h++, n++) {
                    if (n < NLOCAL) continue;
                    const int tile = unit * UNIT + h;
                    if (n == FREE_STAGES) mbar_wait(bar_wfree, 0);
                    mbar_wait(bar_empty + 8 * s, ph);
                    if (tile >= shallow) mbar_wait(bar_empty + 8 * ((s + 1) & 3), s == 3 ? ph ^ 1 : ph);
                    const uint32_t bar = bar_full + 8 * s;
                    tma_load_x_multicast(smem + s * STAGE_BYTES, &tm_x, tile, bar);
                    post_tile(bar, tile_slot + 4 * (n & 31), STAGE_BYTES + 4, tile);
                    post_tile(bar + peer, tile_slot + 4 * (n & 31) + peer, STAGE_BYTES + 4, tile);
                    sts_cluster(progress + peer, unit * UNIT + h * nclusters);
                    if (++s == STAGES) { s = 0; ph ^= 1; }
                    if (late && h == 0) {
                        asm volatile("" : "+r"(next)::"memory");
                        const int succ = next + NSTATIC * nclusters;
                        if (succ >= num_units) {
                            sts(total_slot, n + UNIT);
                            sts_cluster(total_slot + peer, n + UNIT);
                        }
                        if (succ == num_units - 1)
                            asm volatile("st.relaxed.gpu.global.b64 [%0], %1;" ::"l"(&g_dry), "l"(t_fetch) : "memory");
                    }
                }
                asm volatile("" : "+r"(next)::"memory");
                unit = next + NSTATIC * nclusters;
            }
            sts(total_slot, n);
            sts_cluster(total_slot + peer, n);
            sts_cluster(progress + peer, 0x7fffffff);
            mbar_wait(bar_empty + 8 * s, ph);
            post_tile(bar_full + 8 * s, tile_slot + 4 * (n & 31), 4, -1);
            post_tile(bar_full + 8 * s + peer, tile_slot + 4 * (n & 31) + peer, 4, -1);
#pragma unroll 1
            for (int e = 1; e < STAGES; e++) {
                if (++s == STAGES) { s = 0; ph ^= 1; }
                mbar_wait(bar_empty + 8 * s, ph);
            }
        } else if (tid == 448 && rank == 1) {
            auto wait_loader = [&](int tile, uint32_t unless) {
                while (lds(progress) < tile && lds(unless) == 0 && now_ns() - t_entry < 1000000000u) __nanosleep(64);
            };
            const int slope = (RA_LEAD - RA_MIN) * 256 / (RA_END - RA_FADE);
            int lead = RA_LEAD * 256;
            uint32_t due = RA_T0;
#pragma unroll 1
            for (int j = NLOCAL; j / UNIT * nclusters < num_units; j++, due += RA_DT) {
                const int t = even_tile(j);
                if (j >= RA_FADE && j < RA_END) lead -= slope;
                wait_loader(cluster_id * UNIT + j * nclusters - (lead * nclusters >> 10), dry_slot);
                while (now_ns() - t_entry < due) {}
                if (t < ntiles) l2_prefetch_tile(&tm_p, t);
            }
            wait_loader(0x7fffffff, zero_slot);
        } else if (tid == 384 || tid == 448) {
            const unsigned long long t_start = now_ns64();
            for (uint32_t it = 0; it < (1u << 22); it++) {
                unsigned long long v;
                asm volatile("ld.relaxed.gpu.global.b64 %0, [%1];" : "=l"(v) : "l"(&g_dry) : "memory");
                if (v > t_start) { sts(dry_slot, (uint32_t)v | 1); break; }
                if (lds(dry_slot)) break;
                __nanosleep(200);
            }
            if (atomicInc(&g_seen, gridDim.x - 1) == gridDim.x - 1)
                asm volatile("st.relaxed.gpu.global.b64 [%0], %1;" ::"l"(&g_dry), "l"(0ull) : "memory");
        } else if ((tid & 63) == 32) {
            uint32_t base = smem;
            asm volatile("" : "+r"(base));
            const uint32_t ofull = base + (bar_ofull - smem), otile = base + (tile_slot - smem);
            const uint32_t total_at = base + (total_slot - smem);
            int k = (tid >> 6) & 1;
            auto wait_filled = [&](int j) -> bool {
                const uint32_t lap = (uint32_t)j / NBUF, bar = ofull + 8 * (j - lap * NBUF);
                for (uint32_t it = 0; it < (1u << 22); it++) {
                    if (mbar_try(bar, lap & 1)) return true;
                    const int total = lds(total_at);
                    if (total != 0 && j >= total) break;
                }
                return false;
            };
            auto test_filled = [&](int j) -> bool {
                const uint32_t lap = (uint32_t)j / NBUF;
                return mbar_test(ofull + 8 * (j - lap * NBUF), lap & 1);
            };
            const int skew = cluster_id & 1;
            auto trigger = [&]() -> int { return k + min(max(0, RAMP_0 + (k + skew) * RAMP_Q) >> 4, NBUF - 1); };
            auto store = [&]() -> int {
                const int tile = lds(otile + 4 * (k & 31));
                const uint32_t slot = (uint32_t)k % NBUF;
                tma_store_out(&tm_o, base + SMEM_OUT + slot * OUT_BYTES, rank * 3, tile);
                asm volatile("cp.async.bulk.wait_group.read 0;" ::: "memory");
                mbar_arrive(ofull + 8 * (NBUF + slot));
                k += 2;
                return tile;
            };
            const int near_end = ntiles - (KREG + 2 * NBUF) * nclusters;
            while (wait_filled(trigger()))
                if (store() >= near_end) break;
            uint32_t t_dry = 0, due = 0;
            for (uint32_t it = 0; it < (1u << 22); it++) {
                int total = lds(total_at);
                const int m = trigger();
                if ((total == 0 || m < total) && test_filled(m)) { store(); continue; }
                t_dry = lds(base + (dry_slot - smem));
                if (t_dry) {
                    if (total == 0) total = m + KREG + STAGES + DRAIN_PRE;
                    due = t_dry + max(DRAIN_T0, DRAIN_END - (total - k) * DRAIN_DT);
                    if ((int)(now_ns() - due) >= 0) break;
                } else if (total != 0 && total <= m + 1 && test_filled(total - 1)) {
                    break;
                }
            }
            if (!t_dry) {
                due = now_ns();
                t_dry = (due - DRAIN_END) | 1;
                sts(base + (dry_slot - smem), t_dry);
            }
            uint32_t prev = base + (bar_spare - smem) + 8 * (k & 1);
            while (true) {
                const int total = lds(total_at);
                if (total != 0) {
                    if (k >= total) break;
                    due = t_dry + DRAIN_END - (total - k) * DRAIN_DT;
                }
                if (!wait_filled(k)) break;
                const int tile = lds(otile + 4 * (k & 31));
                const uint32_t slot = (uint32_t)k % NBUF;
                while ((int)(now_ns() - due) < 0) {}
                tma_store_out(&tm_o, base + SMEM_OUT + slot * OUT_BYTES, rank * 3, tile);
                asm volatile("cp.async.bulk.wait_group.read 1;" ::: "memory");
                mbar_arrive(prev);
                prev = ofull + 8 * (NBUF + slot);
                k += 2;
                due += 2 * DRAIN_DT;
            }
            asm volatile("cp.async.bulk.wait_group.read 0;" ::: "memory");
        }
    } else {
        asm volatile("setmaxnreg.inc.sync.aligned.u32 160;");
        const int lane = tid & 31;
        const int warp = (tid >> 5) & 3;
        if (wg == 2) asm volatile("bar.arrive 8, 256;" ::: "memory");

        uint32_t bias2;
        {
            const unsigned short* bp =
                reinterpret_cast<const unsigned short*>(bias) + rank * 192 + wg * 64 + warp * 16 + (lane >> 2);
            const uint32_t b0 = bp[0], b1 = bp[8];
            bias2 = b0 | (b1 << 16);
        }
        const uint32_t swz = (uint32_t)(((warp * 2 + ((lane >> 3) & 1)) ^ (lane & 7)) << 4);
        const uint32_t lead = mapa(smem, 0) - smem;

        uint32_t a[24][4];
        asm volatile("barrier.cluster.wait.aligned;" ::: "memory");
        mbar_wait(bar_w + 8 * wg, 0);
        {
            const uint32_t base = smem + SMEM_W + wg * SLAB_BYTES + ((lane >> 4) * 8 + (lane & 7)) * 128 + swz;
#pragma unroll
            for (int ks = 0; ks < 24; ks++)
                asm volatile("ldmatrix.sync.aligned.m8n8.x4.trans.shared.b16 {%0,%1,%2,%3}, [%4];"
                             : "=r"(a[ks][0]), "=r"(a[ks][1]), "=r"(a[ks][2]), "=r"(a[ks][3])
                             : "r"(base + ks * 2048) : "memory");
        }
        fence_async_smem();
        __syncwarp();
        if (lane == 0) {
            mbar_arrive_cluster(bar_wfree + lead);
            mbar_arrive(bar_wloc);
        }

        uint32_t st_base = smem + SMEM_OUT + wg * 1024 + (lane >> 4) * 3072 + (lane & 7) * 128 + swz;
        const int wgu = __shfl_sync(0xffffffffu, wg, 0);
        asm volatile("" : "+r"(st_base), "+r"(bias2));
        const uint64_t desc0 = (uint64_t)((smem & 0x3FFFF) >> 4) | (1ull << 16) | ((6144ull >> 4) << 32) | (1ull << 62);

        int s = 0, ob = 0, i = 0;
        uint32_t ph = 0, oph = 1;
        float d[16];
        uint32_t q[KREG][8];
        auto compute = [&]() -> bool {
            mbar_wait(bar_full + 8 * s, ph);
            if (lds(tile_slot + 4 * (i & 31)) < 0) return false;
            const uint64_t desc = desc0 + (uint64_t)(s * (STAGE_BYTES >> 4));
            asm volatile("bar.sync %0, 256;" ::"r"(8 + wgu) : "memory");
            asm volatile("wgmma.fence.sync.aligned;" ::: "memory");
#pragma unroll
            for (int ks = 0; ks < 24; ks++) {
                wgmma_rs(d, a[ks], desc + (uint64_t)(((ks >> 2) * 1024 + (ks & 3) * 32) >> 4), ks != 0);
                if (ks == HANDOVER - 1) asm volatile("bar.arrive %0, 256;" ::"r"(wgu == 2 ? 8 : 9 + wgu) : "memory");
            }
            asm volatile("wgmma.commit_group.sync.aligned;" ::: "memory");
            asm volatile("wgmma.wait_group.sync.aligned 0;" ::: "memory");
#pragma unroll
            for (int j = 0; j < 16; j++) asm volatile("" : "+f"(d[j])::"memory");
            if (lane == 0) mbar_arrive_cluster(bar_empty + 8 * s + lead);
            if (++s == STAGES) { s = 0; ph ^= 1; }
            return true;
        };
        auto pack = [&](uint32_t (&p)[8]) {
#pragma unroll
            for (int j = 0; j < 8; j += 2) {
                p[j]     = cvt_add_bias<false>(d[2 * j], d[2 * j + 1], bias2);
                p[j + 1] = cvt_add_bias<true>(d[2 * j + 2], d[2 * j + 3], bias2);
            }
        };
        auto put = [&](uint32_t st, const uint32_t (&p)[8]) {
#pragma unroll
            for (int j = 0; j < 2; j++)
                asm volatile("stmatrix.sync.aligned.m8n8.x4.trans.shared.b16 [%0], {%1,%2,%3,%4};"
                             ::"r"(st + j * 6144), "r"(p[4 * j]), "r"(p[4 * j + 1]), "r"(p[4 * j + 2]), "r"(p[4 * j + 3])
                             : "memory");
        };
        auto acquire = [&]() -> uint32_t {
            mbar_wait(bar_oempty + 8 * ob, oph);
            return st_base + ob * OUT_BYTES;
        };
        auto publish = [&]() {
            fence_async_smem();
            __syncwarp();
            if (lane == 0) mbar_arrive(bar_ofull + 8 * ob);
            if (++ob == NBUF) { ob = 0; oph ^= 1; }
        };

        const int kstart = KSTART - cluster_id % KRAMP;
        int held = 0, h = 0;
        bool more = true;
#pragma unroll 1
        for (; i < kstart; i++) {
            more = compute();
            if (!more) break;
            pack(q[0]);
            if (i == 0) mbar_wait(bar_wloc, 0);
            put(acquire(), q[0]);
            publish();
        }
        if (more) {
            int kstep = kstart;
#pragma unroll 1
            for (; compute(); i++) {
                if (h == 0 && i >= kstep) {
#pragma unroll
                    for (int k = 0; k < KREG; k++)
                        if (held == k) pack(q[k]);
                    kstep = ++held == KREG ? 0x7fffffff : kstep + KRAMP;
                    continue;
                }
                const uint32_t st = acquire();
#pragma unroll
                for (int k = 0; k < KREG; k++)
                    if (h == k) { put(st, q[k]); pack(q[k]); }
                publish();
                if (++h == held) h = 0;
            }
#pragma unroll 1
            for (int left = held; left > 0; left--) {
                const uint32_t st = acquire();
#pragma unroll
                for (int k = 0; k < KREG; k++)
                    if (h == k) put(st, q[k]);
                publish();
                if (++h == held) h = 0;
            }
        }
        if (wg == 0) asm volatile("bar.sync 8, 256;" ::: "memory");
    }
}

typedef CUresult (*EncodeTiledFn)(CUtensorMap*, CUtensorMapDataType, cuuint32_t, void*, const cuuint64_t*,
                                  const cuuint64_t*, const cuuint32_t*, const cuuint32_t*, CUtensorMapInterleave,
                                  CUtensorMapSwizzle, CUtensorMapL2promotion, CUtensorMapFloatOOBfill);

void encode_map(EncodeTiledFn fn, CUtensorMap* tm, const void* ptr, int rank, const cuuint64_t* dims,
                const cuuint64_t* strides, const cuuint32_t* box) {
    const cuuint32_t estr[4] = {1, 1, 1, 1};
    fn(tm, CU_TENSOR_MAP_DATA_TYPE_BFLOAT16, rank, const_cast<void*>(ptr), dims, strides, box, estr,
       CU_TENSOR_MAP_INTERLEAVE_NONE, CU_TENSOR_MAP_SWIZZLE_128B, CU_TENSOR_MAP_L2_PROMOTION_L2_128B,
       CU_TENSOR_MAP_FLOAT_OOB_FILL_NONE);
}

}

extern "C" void kernel_launch(void* const* d_in, const int* in_sizes, int n_in, void* d_out, int out_size) {
    const __nv_bfloat16* x = (const __nv_bfloat16*)d_in[0];
    const __nv_bfloat16* w = (const __nv_bfloat16*)d_in[1];
    const __nv_bfloat16* b = (const __nv_bfloat16*)d_in[2];
    const int pixels = in_sizes[0] / C;

    static EncodeTiledFn encode = nullptr;
    static int max_clusters = 0;
    if (!encode) {
        void* fn = nullptr;
        cudaDriverEntryPointQueryResult qr;
        cudaGetDriverEntryPoint("cuTensorMapEncodeTiled", &fn, cudaEnableDefault, &qr);
        encode = (EncodeTiledFn)fn;
        cudaFuncSetAttribute(conv1x1_kernel, cudaFuncAttributeMaxDynamicSharedMemorySize, SMEM_TOTAL);
        cudaLaunchConfig_t cfg = {};
        cfg.gridDim = dim3(2, 1, 1);
        cfg.blockDim = dim3(NTHREADS, 1, 1);
        cfg.dynamicSmemBytes = SMEM_TOTAL;
        cudaLaunchAttribute at[1];
        at[0].id = cudaLaunchAttributeClusterDimension;
        at[0].val.clusterDim.x = 2; at[0].val.clusterDim.y = 1; at[0].val.clusterDim.z = 1;
        cfg.attrs = at; cfg.numAttrs = 1;
        if (cudaOccupancyMaxActiveClusters(&max_clusters, conv1x1_kernel, &cfg) != cudaSuccess || max_clusters <= 0) {
            (void)cudaGetLastError();
            int dev = 0, sms = 0;
            cudaGetDevice(&dev);
            cudaDeviceGetAttribute(&sms, cudaDevAttrMultiProcessorCount, dev);
            max_clusters = sms / 2;
        }
    }
    CUtensorMap tm_x, tm_w, tm_o, tm_p;
    {
        const cuuint64_t dims[4]    = {64, 8, 6, (cuuint64_t)(pixels / 8)};
        const cuuint64_t strides[3] = {C * 2, 128, C * 2 * 8};
        const cuuint32_t box_x[4]   = {64, 8, 6, TP / 8};
        const cuuint32_t box_o[4]   = {64, 8, 3, TP / 8};
        encode_map(encode, &tm_x, x, 4, dims, strides, box_x);
        encode_map(encode, &tm_o, d_out, 4, dims, strides, box_o);
        const cuuint64_t pdims[2]    = {64, (cuuint64_t)pixels * 6};
        const cuuint64_t pstrides[1] = {128};
        const cuuint32_t pbox[2]     = {64, STAGE_BYTES / 128};
        encode_map(encode, &tm_p, x, 2, pdims, pstrides, pbox);
        const cuuint64_t wdims[3]    = {C, 192, 2};
        const cuuint64_t wstrides[2] = {C * 2, C * 2 * 192};
        const cuuint32_t wbox[3]     = {64, 192, 2};
        encode_map(encode, &tm_w, w, 3, wdims, wstrides, wbox);
    }
    const int num_units = pixels / (TP * UNIT);
    const int nclusters = max_clusters * NSTATIC <= num_units ? max_clusters : num_units / NSTATIC;
    conv1x1_kernel<<<2 * nclusters, NTHREADS, SMEM_TOTAL, cudaStreamPerThread>>>(x, w, b, num_units, tm_x, tm_w, tm_o, tm_p);
}
```

```cpp
#include <cuda_runtime.h>
#include <cuda_bf16.h>
#include <cuda.h>
#include <stdint.h>

#define TUNE(name, value) constexpr int name = value
TUNE(RAMP_Q, 11);
TUNE(RAMP_0, -13);
TUNE(KSTART, 27);
TUNE(KRAMP, 4);
TUNE(EARLY_N, 4);
TUNE(EARLY_T, 415);
TUNE(EARLY_DT, 320);
TUNE(RA_T0, 1740);
TUNE(RA_DT, 456);
TUNE(RA_LEAD, 40);
TUNE(RA_FADE, 10);
TUNE(RA_END, 63);
TUNE(RA_MIN, 8);
TUNE(SHALLOW, 11);
TUNE(DRAIN_T0, 300);
TUNE(DRAIN_END, 11150);
TUNE(DRAIN_DT, 468);
TUNE(DRAIN_PRE, 2);

namespace {

constexpr int C           = 384;
constexpr int TP          = 32;
constexpr int UNIT        = 2;
constexpr int NSTATIC     = 4;
constexpr int KREG        = 5;
constexpr int HANDOVER    = 18;
constexpr int STAGES      = 4;
constexpr int NBUF        = 10;
constexpr int NLOCAL      = 2;
constexpr int STAGE_BYTES = TP * C * 2;
constexpr int OUT_BYTES   = TP * 192 * 2;
constexpr int SLAB_BYTES  = C * 64 * 2;
constexpr int SMEM_OUT    = STAGES * STAGE_BYTES;
constexpr int SMEM_BAR    = SMEM_OUT + NBUF * OUT_BYTES;
constexpr int SMEM_TOTAL  = SMEM_BAR + 512 + 1024;
constexpr int NTHREADS    = 512;
constexpr int SMEM_W      = SMEM_BAR - 3 * SLAB_BYTES;
constexpr int FREE_STAGES = SMEM_W / STAGE_BYTES;
static_assert(SMEM_W % 1024 == 0 && NLOCAL <= FREE_STAGES && FREE_STAGES < NSTATIC * UNIT, "layout");
static_assert(STAGES == 4 && NSTATIC * UNIT >= STAGES, "the shallow mode of the loader assumes four stages");
static_assert(SMEM_TOTAL <= 232448, "too much shared memory");

__device__ unsigned int g_sched;
__device__ unsigned long long g_dry;
__device__ unsigned int g_seen;

__device__ __forceinline__ uint32_t smem_u32(const void* p) { return (uint32_t)__cvta_generic_to_shared(p); }
__device__ __forceinline__ uint32_t now_ns() {
    uint32_t t;
    asm volatile("mov.u32 %0, %%globaltimer_lo;" : "=r"(t));
    return t;
}
__device__ __forceinline__ unsigned long long now_ns64() {
    unsigned long long t;
    asm volatile("mov.u64 %0, %%globaltimer;" : "=l"(t));
    return t;
}
__device__ __forceinline__ int lds(uint32_t addr) {
    int v;
    asm volatile("ld.volatile.shared.b32 %0, [%1];" : "=r"(v) : "r"(addr) : "memory");
    return v;
}
__device__ __forceinline__ void sts(uint32_t addr, int v) {
    asm volatile("st.volatile.shared.b32 [%0], %1;" ::"r"(addr), "r"(v) : "memory");
}
__device__ __forceinline__ void sts_cluster(uint32_t cluster_addr, int v) {
    asm volatile("st.volatile.shared::cluster.b32 [%0], %1;" ::"r"(cluster_addr), "r"(v) : "memory");
}
__device__ __forceinline__ void mbar_init(uint32_t bar, uint32_t count) {
    asm volatile("mbarrier.init.shared::cta.b64 [%0], %1;" ::"r"(bar), "r"(count) : "memory");
}
__device__ __forceinline__ void mbar_expect_tx(uint32_t bar, uint32_t bytes) {
    asm volatile("mbarrier.arrive.expect_tx.shared::cta.b64 _, [%0], %1;" ::"r"(bar), "r"(bytes) : "memory");
}
__device__ __forceinline__ void mbar_arrive(uint32_t bar) {
    asm volatile("mbarrier.arrive.shared::cta.b64 _, [%0];" ::"r"(bar) : "memory");
}
__device__ __forceinline__ void mbar_arrive_cluster(uint32_t cluster_addr) {
    asm volatile("mbarrier.arrive.shared::cluster.b64 _, [%0];" ::"r"(cluster_addr) : "memory");
}
__device__ __forceinline__ bool mbar_try(uint32_t bar, uint32_t parity) {
    uint32_t ok;
    asm volatile("{\n.reg .pred p;\nmbarrier.try_wait.parity.shared::cta.b64 p, [%1], %2;\nselp.u32 %0, 1, 0, p;\n}"
                 : "=r"(ok) : "r"(bar), "r"(parity) : "memory");
    return ok;
}
__device__ __forceinline__ bool mbar_test(uint32_t bar, uint32_t parity) {
    uint32_t ok;
    asm volatile("{\n.reg .pred p;\nmbarrier.test_wait.parity.shared::cta.b64 p, [%1], %2;\nselp.u32 %0, 1, 0, p;\n}"
                 : "=r"(ok) : "r"(bar), "r"(parity) : "memory");
    return ok;
}
__device__ __forceinline__ void mbar_wait(uint32_t bar, uint32_t parity) {
    asm volatile("{\n.reg .pred p, q;\n.reg .u32 n;\n"
                 "mbarrier.try_wait.parity.shared::cta.b64 p, [%0], %1;\n@p bra DONE;\nmov.u32 n, 0;\n"
                 "AGAIN:\nmbarrier.try_wait.parity.shared::cta.b64 p, [%0], %1;\nadd.u32 n, n, 1;\n"
                 "setp.lt.and.u32 q, n, 0x400000, !p;\n@q bra AGAIN;\nDONE:\n}"
                 ::"r"(bar), "r"(parity) : "memory");
}
__device__ __forceinline__ uint32_t mapa(uint32_t addr, uint32_t rank) {
    uint32_t r;
    asm("mapa.shared::cluster.u32 %0, %1, %2;" : "=r"(r) : "r"(addr), "r"(rank));
    return r;
}
__device__ __forceinline__ void fence_async_smem() { asm volatile("fence.proxy.async.shared::cta;" ::: "memory"); }
__device__ __forceinline__ void post_tile(uint32_t bar, uint32_t slot, uint32_t bytes, int value) {
    asm volatile("mbarrier.arrive.expect_tx.shared::cluster.b64 _, [%0], %1;" ::"r"(bar), "r"(bytes) : "memory");
    asm volatile("st.async.weak.shared::cluster.mbarrier::complete_tx::bytes.b32 [%0], %1, [%2];"
                 ::"r"(slot), "r"(value), "r"(bar) : "memory");
}
__device__ __forceinline__ void tma_load_w(uint32_t dst, const CUtensorMap* tm, int ch, uint32_t bar) {
    asm volatile("cp.async.bulk.tensor.3d.shared::cluster.global.mbarrier::complete_tx::bytes [%0], [%1, {%3, %4, %4}], [%2];"
                 ::"r"(dst), "l"(tm), "r"(bar), "r"(ch), "r"(0) : "memory");
}
__device__ __forceinline__ void tma_load_x(uint32_t dst, const CUtensorMap* tm, int tile, uint32_t bar) {
    asm volatile("cp.async.bulk.tensor.4d.shared::cluster.global.mbarrier::complete_tx::bytes"
                 " [%0], [%1, {%4, %4, %4, %3}], [%2];"
                 ::"r"(dst), "l"(tm), "r"(bar), "r"(tile * (TP / 8)), "r"(0) : "memory");
}
__device__ __forceinline__ void tma_load_x_multicast(uint32_t dst, const CUtensorMap* tm, int tile, uint32_t bar) {
    asm volatile("cp.async.bulk.tensor.4d.shared::cluster.global.mbarrier::complete_tx::bytes.multicast::cluster"
                 " [%0], [%1, {%4, %4, %4, %3}], [%2], %5;"
                 ::"r"(dst), "l"(tm), "r"(bar), "r"(tile * (TP / 8)), "r"(0), "h"((uint16_t)3) : "memory");
}
__device__ __forceinline__ void tma_store_out(const CUtensorMap* tm, uint32_t src, int slab, int tile) {
    asm volatile("cp.async.bulk.tensor.4d.global.shared::cta.bulk_group [%0, {%4, %4, %2, %3}], [%1];"
                 ::"l"(tm), "r"(src), "r"(slab), "r"(tile * (TP / 8)), "r"(0) : "memory");
    asm volatile("cp.async.bulk.commit_group;" ::: "memory");
}
__device__ __forceinline__ void l2_prefetch_tile(const CUtensorMap* tm, int tile) {
    asm volatile("cp.async.bulk.prefetch.tensor.2d.L2.global.tile [%0, {%1, %2}];"
                 ::"l"(tm), "r"(0), "r"(tile * (STAGE_BYTES / 128)) : "memory");
}

__device__ __forceinline__ void wgmma_rs(float (&d)[16], const uint32_t (&a)[4], uint64_t desc, int scale_d) {
    asm volatile(
        "{\n.reg .pred p;\nsetp.ne.b32 p, %21, 0;\n"
        "wgmma.mma_async.sync.aligned.m64n32k16.f32.bf16.bf16 "
        "{%0,%1,%2,%3,%4,%5,%6,%7,%8,%9,%10,%11,%12,%13,%14,%15},"
        "{%16,%17,%18,%19}, %20, p, 1, 1, 0;\n}"
        : "+f"(d[0]), "+f"(d[1]), "+f"(d[2]), "+f"(d[3]), "+f"(d[4]), "+f"(d[5]), "+f"(d[6]), "+f"(d[7]),
          "+f"(d[8]), "+f"(d[9]), "+f"(d[10]), "+f"(d[11]), "+f"(d[12]), "+f"(d[13]), "+f"(d[14]), "+f"(d[15])
        : "r"(a[0]), "r"(a[1]), "r"(a[2]), "r"(a[3]), "l"(desc), "r"(scale_d));
}
template <bool HI>
__device__ __forceinline__ uint32_t cvt_add_bias(float lo, float hi, uint32_t bias2) {
    uint32_t r;
    if (HI) asm("{\n.reg .b32 t, b;\n.reg .b16 l, h;\ncvt.rn.bf16x2.f32 t, %2, %1;\nmov.b32 {l, h}, %3;\nmov.b32 b, {h, h};\n"
                "add.rn.bf16x2 %0, t, b;\n}" : "=r"(r) : "f"(lo), "f"(hi), "r"(bias2));
    else asm("{\n.reg .b32 t, b;\n.reg .b16 l, h;\ncvt.rn.bf16x2.f32 t, %2, %1;\nmov.b32 {l, h}, %3;\nmov.b32 b, {l, l};\n"
             "add.rn.bf16x2 %0, t, b;\n}" : "=r"(r) : "f"(lo), "f"(hi), "r"(bias2));
    return r;
}

__global__ void __cluster_dims__(2, 1, 1) __launch_bounds__(NTHREADS, 1)
conv1x1_kernel(const __nv_bfloat16* __restrict__ x, const __nv_bfloat16* __restrict__ w,
               const __nv_bfloat16* __restrict__ bias, int num_units,
               const __grid_constant__ CUtensorMap tm_x, const __grid_constant__ CUtensorMap tm_w,
               const __grid_constant__ CUtensorMap tm_o, const __grid_constant__ CUtensorMap tm_p) {
    extern __shared__ uint8_t smem_raw[];
    const uint32_t smem = (smem_u32(smem_raw) + 1023u) & ~1023u;
    const uint32_t bar_full   = smem + SMEM_BAR;
    const uint32_t bar_empty  = bar_full + 8 * STAGES;
    const uint32_t bar_ofull  = bar_empty + 8 * STAGES;
    const uint32_t bar_oempty = bar_ofull + 8 * NBUF;
    const uint32_t bar_w      = bar_oempty + 8 * NBUF;
    const uint32_t bar_wfree  = bar_w + 24;
    const uint32_t bar_wloc   = bar_wfree + 8;
    const uint32_t bar_spare  = bar_wloc + 8;
    const uint32_t progress   = bar_spare + 16;
    const uint32_t total_slot = progress + 4;
    const uint32_t dry_slot   = progress + 8;
    const uint32_t zero_slot  = progress + 12;
    const uint32_t tile_slot  = progress + 16;

    const int tid = threadIdx.x;
    const int wg  = tid >> 7;
    uint32_t rank;
    asm("mov.u32 %0, %%cluster_ctarank;" : "=r"(rank));
    const int cluster_id = blockIdx.x >> 1;
    const int nclusters  = gridDim.x >> 1;
    const int ntiles     = num_units * UNIT;
    auto even_tile = [&](int j) { return (cluster_id + j / UNIT * nclusters) * UNIT + j % UNIT; };

    asm volatile("setmaxnreg.dec.sync.aligned.u32 32;");

    auto prefetch_lines = [&](const void* base, int bytes) {
        const char* p = static_cast<const char*>(base) + (tid & 31) * 128;
#pragma unroll
        for (int o = 0; o < bytes; o += 4096)
            if (o + 4096 <= bytes || (tid & 31) * 128 < bytes - o)
                asm volatile("prefetch.global.L2 [%0];" ::"l"(p + o) : "memory");
    };
    auto prefetch_half_tile = [&](int j) {
        prefetch_lines(x + (size_t)(even_tile(j) * TP + rank * (TP / 2)) * C, STAGE_BYTES / 2);
    };
    uint32_t t_entry = 0;
    if ((tid >> 5) == 14) {
        prefetch_lines(w + (blockIdx.x & 63) * (C * C / 64), C * C * 2 / 64);
        prefetch_half_tile(0);
        t_entry = now_ns();
        if (tid == 448) asm volatile("prefetch.tensormap [%0];" ::"l"(&tm_p) : "memory");
    }
    if (tid == 384) {
        asm volatile("prefetch.tensormap [%0];" ::"l"(&tm_w) : "memory");
        asm volatile("prefetch.tensormap [%0];" ::"l"(&tm_x) : "memory");
        for (int g = 0; g < 3; g++) mbar_init(bar_w + 8 * g, 1);
        for (int s = 0; s < NLOCAL; s++) mbar_init(bar_full + 8 * s, 1);
        asm volatile("fence.mbarrier_init.release.cluster;" ::: "memory");
        fence_async_smem();
        for (int g = 0; g < 3; g++) {
            mbar_expect_tx(bar_w + 8 * g, SLAB_BYTES);
            tma_load_w(smem + SMEM_W + g * SLAB_BYTES, &tm_w, rank * 192 + g * 64, bar_w + 8 * g);
        }
        for (int s = 0; s < NLOCAL; s++) {
            sts(tile_slot + 4 * s, even_tile(s));
            mbar_expect_tx(bar_full + 8 * s, STAGE_BYTES);
            tma_load_x(smem + s * STAGE_BYTES, &tm_x, even_tile(s), bar_full + 8 * s);
        }
    }
    if (tid == 416) {
        for (int s = NLOCAL; s < STAGES; s++) mbar_init(bar_full + 8 * s, 1);
        for (int s = 0; s < STAGES; s++) mbar_init(bar_empty + 8 * s, 24);
        for (int s = 0; s < NBUF; s++) {
            mbar_init(bar_ofull + 8 * s, 12);
            mbar_init(bar_oempty + 8 * s, 1);
        }
        mbar_init(bar_wfree, 24);
        mbar_init(bar_wloc, 12);
        mbar_init(bar_spare, 1);
        mbar_init(bar_spare + 8, 1);
        sts(progress, 0);
        sts(total_slot, 0);
        sts(dry_slot, 0);
        sts(zero_slot, 0);
        asm volatile("fence.mbarrier_init.release.cluster;" ::: "memory");
        fence_async_smem();
        asm volatile("prefetch.tensormap [%0];" ::"l"(&tm_o) : "memory");
    }
    __syncwarp();
    asm volatile("barrier.cluster.arrive.relaxed.aligned;" ::: "memory");

    if (wg == 3) {
        if ((tid >> 5) == 14) {
            uint32_t due = EARLY_T;
#pragma unroll 1
            for (int j = 1; j < EARLY_N; j++, due += EARLY_DT) {
                while (now_ns() - t_entry < due) {}
                prefetch_half_tile(j);
            }
        }
        __syncwarp();
        asm volatile("barrier.cluster.wait.aligned;" ::: "memory");
        if (tid == 384 && rank == 0) {
            const uint32_t peer = mapa(smem, 1) - smem;
            const int shallow = max(ntiles - SHALLOW * nclusters, NSTATIC * UNIT * nclusters);
            int s = NLOCAL, n = 0;
            uint32_t ph = 1;
            int unit = cluster_id;
            for (int u = 0; unit < num_units; u++) {
                const bool late = unit * UNIT >= ntiles - 6 * nclusters;
                const unsigned long long t_fetch = late ? now_ns64() : 0;
                int next = unit - (NSTATIC - 1) * nclusters;
                if (u >= NSTATIC - 1) next = (int)atomicInc(&g_sched, (unsigned)(num_units - (NSTATIC - 1) * nclusters - 1));
#pragma unroll 1
                for (int h = 0; h < UNIT; h++, n++) {
                    if (n < NLOCAL) continue;
                    const int tile = unit * UNIT + h;
                    if (n == FREE_STAGES) mbar_wait(bar_wfree, 0);
                    mbar_wait(bar_empty + 8 * s, ph);
                    if (tile >= shallow) mbar_wait(bar_empty + 8 * ((s + 1) & 3), s == 3 ? ph ^ 1 : ph);
                    const uint32_t bar = bar_full + 8 * s;
                    tma_load_x_multicast(smem + s * STAGE_BYTES, &tm_x, tile, bar);
                    post_tile(bar, tile_slot + 4 * (n & 31), STAGE_BYTES + 4, tile);
                    post_tile(bar + peer, tile_slot + 4 * (n & 31) + peer, STAGE_BYTES + 4, tile);
                    sts_cluster(progress + peer, unit * UNIT + h * nclusters);
                    if (++s == STAGES) { s = 0; ph ^= 1; }
                    if (late && h == 0) {
                        asm volatile("" : "+r"(next)::"memory");
                        const int succ = next + NSTATIC * nclusters;
                        if (succ >= num_units) {
                            sts(total_slot, n + UNIT);
                            sts_cluster(total_slot + peer, n + UNIT);
                        }
                        if (succ == num_units - 1)
                            asm volatile("st.relaxed.gpu.global.b64 [%0], %1;" ::"l"(&g_dry), "l"(t_fetch) : "memory");
                    }
                }
                asm volatile("" : "+r"(next)::"memory");
                unit = next + NSTATIC * nclusters;
            }
            sts(total_slot, n);
            sts_cluster(total_slot + peer, n);
            sts_cluster(progress + peer, 0x7fffffff);
            mbar_wait(bar_empty + 8 * s, ph);
            post_tile(bar_full + 8 * s, tile_slot + 4 * (n & 31), 4, -1);
            post_tile(bar_full + 8 * s + peer, tile_slot + 4 * (n & 31) + peer, 4, -1);
#pragma unroll 1
            for (int e = 1; e < STAGES; e++) {
                if (++s == STAGES) { s = 0; ph ^= 1; }
                mbar_wait(bar_empty + 8 * s, ph);
            }
        } else if (tid == 448 && rank == 1) {
            auto wait_loader = [&](int tile, uint32_t unless) {
                while (lds(progress) < tile && lds(unless) == 0 && now_ns() - t_entry < 1000000000u) __nanosleep(64);
            };
            const int slope = (RA_LEAD - RA_MIN) * 256 / (RA_END - RA_FADE);
            int lead = RA_LEAD * 256;
            uint32_t due = RA_T0;
#pragma unroll 1
            for (int j = EARLY_N; j / UNIT * nclusters < num_units; j++, due += RA_DT) {
                const int t = even_tile(j);
                if (j >= RA_FADE && j < RA_END) lead -= slope;
                wait_loader(cluster_id * UNIT + j * nclusters - (lead * nclusters >> 10), dry_slot);
                while (now_ns() - t_entry < due) {}
                if (t < ntiles) l2_prefetch_tile(&tm_p, t);
            }
            wait_loader(0x7fffffff, zero_slot);
        } else if (tid == 384 || tid == 448) {
            const unsigned long long t_start = now_ns64();
            for (uint32_t it = 0; it < (1u << 22); it++) {
                unsigned long long v;
                asm volatile("ld.relaxed.gpu.global.b64 %0, [%1];" : "=l"(v) : "l"(&g_dry) : "memory");
                if (v > t_start) { sts(dry_slot, (uint32_t)v | 1); break; }
                if (lds(dry_slot)) break;
                __nanosleep(200);
            }
            if (atomicInc(&g_seen, gridDim.x - 1) == gridDim.x - 1)
                asm volatile("st.relaxed.gpu.global.b64 [%0], %1;" ::"l"(&g_dry), "l"(0ull) : "memory");
        } else if ((tid & 63) == 32) {
            uint32_t base = smem;
            asm volatile("" : "+r"(base));
            const uint32_t ofull = base + (bar_ofull - smem), otile = base + (tile_slot - smem);
            const uint32_t total_at = base + (total_slot - smem);
            int k = (tid >> 6) & 1;
            auto wait_filled = [&](int j) -> bool {
                const uint32_t lap = (uint32_t)j / NBUF, bar = ofull + 8 * (j - lap * NBUF);
                for (uint32_t it = 0; it < (1u << 22); it++) {
                    if (mbar_try(bar, lap & 1)) return true;
                    const int total = lds(total_at);
                    if (total != 0 && j >= total) break;
                }
                return false;
            };
            auto test_filled = [&](int j) -> bool {
                const uint32_t lap = (uint32_t)j / NBUF;
                return mbar_test(ofull + 8 * (j - lap * NBUF), lap & 1);
            };
            const int skew = cluster_id & 1;
            auto trigger = [&]() -> int { return k + min(max(0, RAMP_0 + (k + skew) * RAMP_Q) >> 4, NBUF - 1); };
            auto store = [&]() -> int {
                const int tile = lds(otile + 4 * (k & 31));
                const uint32_t slot = (uint32_t)k % NBUF;
                tma_store_out(&tm_o, base + SMEM_OUT + slot * OUT_BYTES, rank * 3, tile);
                asm volatile("cp.async.bulk.wait_group.read 0;" ::: "memory");
                mbar_arrive(ofull + 8 * (NBUF + slot));
                k += 2;
                return tile;
            };
            const int near_end = ntiles - (KREG + 2 * NBUF) * nclusters;
            while (wait_filled(trigger()))
                if (store() >= near_end) break;
            uint32_t t_dry = 0, due = 0;
            for (uint32_t it = 0; it < (1u << 22); it++) {
                int total = lds(total_at);
                const int m = trigger();
                if ((total == 0 || m < total) && test_filled(m)) { store(); continue; }
                t_dry = lds(base + (dry_slot - smem));
                if (t_dry) {
                    if (total == 0) total = m + KREG + STAGES + DRAIN_PRE;
                    due = t_dry + max(DRAIN_T0, DRAIN_END - (total - k) * DRAIN_DT);
                    if ((int)(now_ns() - due) >= 0) break;
                } else if (total != 0 && total <= m + 1 && test_filled(total - 1)) {
                    break;
                }
            }
            if (!t_dry) {
                due = now_ns();
                t_dry = (due - DRAIN_END) | 1;
                sts(base + (dry_slot - smem), t_dry);
            }
            uint32_t prev = base + (bar_spare - smem) + 8 * (k & 1);
            while (true) {
                const int total = lds(total_at);
                if (total != 0) {
                    if (k >= total) break;
                    due = t_dry + DRAIN_END - (total - k) * DRAIN_DT;
                }
                if (!wait_filled(k)) break;
                const int tile = lds(otile + 4 * (k & 31));
                const uint32_t slot = (uint32_t)k % NBUF;
                while ((int)(now_ns() - due) < 0) {}
                tma_store_out(&tm_o, base + SMEM_OUT + slot * OUT_BYTES, rank * 3, tile);
                asm volatile("cp.async.bulk.wait_group.read 1;" ::: "memory");
                mbar_arrive(prev);
                prev = ofull + 8 * (NBUF + slot);
                k += 2;
                due += 2 * DRAIN_DT;
            }
            asm volatile("cp.async.bulk.wait_group.read 0;" ::: "memory");
        }
    } else {
        asm volatile("setmaxnreg.inc.sync.aligned.u32 160;");
        const int lane = tid & 31;
        const int warp = (tid >> 5) & 3;
        if (wg == 2) asm volatile("bar.arrive 8, 256;" ::: "memory");

        uint32_t bias2;
        {
            const unsigned short* bp =
                reinterpret_cast<const unsigned short*>(bias) + rank * 192 + wg * 64 + warp * 16 + (lane >> 2);
            const uint32_t b0 = bp[0], b1 = bp[8];
            bias2 = b0 | (b1 << 16);
        }
        const uint32_t swz = (uint32_t)(((warp * 2 + ((lane >> 3) & 1)) ^ (lane & 7)) << 4);
        const uint32_t lead = mapa(smem, 0) - smem;

        uint32_t a[24][4];
        asm volatile("barrier.cluster.wait.aligned;" ::: "memory");
        mbar_wait(bar_w + 8 * wg, 0);
        {
            const uint32_t base = smem + SMEM_W + wg * SLAB_BYTES + ((lane >> 4) * 8 + (lane & 7)) * 128 + swz;
#pragma unroll
            for (int ks = 0; ks < 24; ks++)
                asm volatile("ldmatrix.sync.aligned.m8n8.x4.trans.shared.b16 {%0,%1,%2,%3}, [%4];"
                             : "=r"(a[ks][0]), "=r"(a[ks][1]), "=r"(a[ks][2]), "=r"(a[ks][3])
                             : "r"(base + ks * 2048) : "memory");
        }
        fence_async_smem();
        __syncwarp();
        if (lane == 0) {
            mbar_arrive_cluster(bar_wfree + lead);
            mbar_arrive(bar_wloc);
        }

        uint32_t st_base = smem + SMEM_OUT + wg * 1024 + (lane >> 4) * 3072 + (lane & 7) * 128 + swz;
        const int wgu = __shfl_sync(0xffffffffu, wg, 0);
        asm volatile("" : "+r"(st_base), "+r"(bias2));
        const uint64_t desc0 = (uint64_t)((smem & 0x3FFFF) >> 4) | (1ull << 16) | ((6144ull >> 4) << 32) | (1ull << 62);

        int s = 0, ob = 0, i = 0;
        uint32_t ph = 0, oph = 1;
        float d[16];
        uint32_t q[KREG][8];
        auto compute = [&]() -> bool {
            mbar_wait(bar_full + 8 * s, ph);
            if (lds(tile_slot + 4 * (i & 31)) < 0) return false;
            const uint64_t desc = desc0 + (uint64_t)(s * (STAGE_BYTES >> 4));
            asm volatile("bar.sync %0, 256;" ::"r"(8 + wgu) : "memory");
            asm volatile("wgmma.fence.sync.aligned;" ::: "memory");
#pragma unroll
            for (int ks = 0; ks < 24; ks++) {
                wgmma_rs(d, a[ks], desc + (uint64_t)(((ks >> 2) * 1024 + (ks & 3) * 32) >> 4), ks != 0);
                if (ks == HANDOVER - 1) asm volatile("bar.arrive %0, 256;" ::"r"(wgu == 2 ? 8 : 9 + wgu) : "memory");
            }
            asm volatile("wgmma.commit_group.sync.aligned;" ::: "memory");
            asm volatile("wgmma.wait_group.sync.aligned 0;" ::: "memory");
#pragma unroll
            for (int j = 0; j < 16; j++) asm volatile("" : "+f"(d[j])::"memory");
            if (lane == 0) mbar_arrive_cluster(bar_empty + 8 * s + lead);
            if (++s == STAGES) { s = 0; ph ^= 1; }
            return true;
        };
        auto pack = [&](uint32_t (&p)[8]) {
#pragma unroll
            for (int j = 0; j < 8; j += 2) {
                p[j]     = cvt_add_bias<false>(d[2 * j], d[2 * j + 1], bias2);
                p[j + 1] = cvt_add_bias<true>(d[2 * j + 2], d[2 * j + 3], bias2);
            }
        };
        auto put = [&](uint32_t st, const uint32_t (&p)[8]) {
#pragma unroll
            for (int j = 0; j < 2; j++)
                asm volatile("stmatrix.sync.aligned.m8n8.x4.trans.shared.b16 [%0], {%1,%2,%3,%4};"
                             ::"r"(st + j * 6144), "r"(p[4 * j]), "r"(p[4 * j + 1]), "r"(p[4 * j + 2]), "r"(p[4 * j + 3])
                             : "memory");
        };
        auto acquire = [&]() -> uint32_t {
            mbar_wait(bar_oempty + 8 * ob, oph);
            return st_base + ob * OUT_BYTES;
        };
        auto publish = [&]() {
            fence_async_smem();
            __syncwarp();
            if (lane == 0) mbar_arrive(bar_ofull + 8 * ob);
            if (++ob == NBUF) { ob = 0; oph ^= 1; }
        };

        const int kstart = KSTART - cluster_id % KRAMP;
        int held = 0, h = 0;
        bool more = true;
#pragma unroll 1
        for (; i < kstart; i++) {
            more = compute();
            if (!more) break;
            pack(q[0]);
            if (i == 0) mbar_wait(bar_wloc, 0);
            put(acquire(), q[0]);
            publish();
        }
        if (more) {
            int kstep = kstart;
#pragma unroll 1
            for (; compute(); i++) {
                if (h == 0 && i >= kstep) {
#pragma unroll
                    for (int k = 0; k < KREG; k++)
                        if (held == k) pack(q[k]);
                    kstep = ++held == KREG ? 0x7fffffff : kstep + KRAMP;
                    continue;
                }
                const uint32_t st = acquire();
#pragma unroll
                for (int k = 0; k < KREG; k++)
                    if (h == k) { put(st, q[k]); pack(q[k]); }
                publish();
                if (++h == held) h = 0;
            }
#pragma unroll 1
            for (int left = held; left > 0; left--) {
                const uint32_t st = acquire();
#pragma unroll
                for (int k = 0; k < KREG; k++)
                    if (h == k) put(st, q[k]);
                publish();
                if (++h == held) h = 0;
            }
        }
        if (wg == 0) asm volatile("bar.sync 8, 256;" ::: "memory");
    }
}

typedef CUresult (*EncodeTiledFn)(CUtensorMap*, CUtensorMapDataType, cuuint32_t, void*, const cuuint64_t*,
                                  const cuuint64_t*, const cuuint32_t*, const cuuint32_t*, CUtensorMapInterleave,
                                  CUtensorMapSwizzle, CUtensorMapL2promotion, CUtensorMapFloatOOBfill);

void encode_map(EncodeTiledFn fn, CUtensorMap* tm, const void* ptr, int rank, const cuuint64_t* dims,
                const cuuint64_t* strides, const cuuint32_t* box) {
    const cuuint32_t estr[4] = {1, 1, 1, 1};
    fn(tm, CU_TENSOR_MAP_DATA_TYPE_BFLOAT16, rank, const_cast<void*>(ptr), dims, strides, box, estr,
       CU_TENSOR_MAP_INTERLEAVE_NONE, CU_TENSOR_MAP_SWIZZLE_128B, CU_TENSOR_MAP_L2_PROMOTION_L2_128B,
       CU_TENSOR_MAP_FLOAT_OOB_FILL_NONE);
}

}

extern "C" void kernel_launch(void* const* d_in, const int* in_sizes, int n_in, void* d_out, int out_size) {
    const __nv_bfloat16* x = (const __nv_bfloat16*)d_in[0];
    const __nv_bfloat16* w = (const __nv_bfloat16*)d_in[1];
    const __nv_bfloat16* b = (const __nv_bfloat16*)d_in[2];
    const int pixels = in_sizes[0] / C;

    static EncodeTiledFn encode = nullptr;
    static int max_clusters = 0;
    if (!encode) {
        void* fn = nullptr;
        cudaDriverEntryPointQueryResult qr;
        cudaGetDriverEntryPoint("cuTensorMapEncodeTiled", &fn, cudaEnableDefault, &qr);
        encode = (EncodeTiledFn)fn;
        cudaFuncSetAttribute(conv1x1_kernel, cudaFuncAttributeMaxDynamicSharedMemorySize, SMEM_TOTAL);
        cudaLaunchConfig_t cfg = {};
        cfg.gridDim = dim3(2, 1, 1);
        cfg.blockDim = dim3(NTHREADS, 1, 1);
        cfg.dynamicSmemBytes = SMEM_TOTAL;
        cudaLaunchAttribute at[1];
        at[0].id = cudaLaunchAttributeClusterDimension;
        at[0].val.clusterDim.x = 2; at[0].val.clusterDim.y = 1; at[0].val.clusterDim.z = 1;
        cfg.attrs = at; cfg.numAttrs = 1;
        if (cudaOccupancyMaxActiveClusters(&max_clusters, conv1x1_kernel, &cfg) != cudaSuccess || max_clusters <= 0) {
            (void)cudaGetLastError();
            int dev = 0, sms = 0;
            cudaGetDevice(&dev);
            cudaDeviceGetAttribute(&sms, cudaDevAttrMultiProcessorCount, dev);
            max_clusters = sms / 2;
        }
    }
    CUtensorMap tm_x, tm_w, tm_o, tm_p;
    {
        const cuuint64_t dims[4]    = {64, 8, 6, (cuuint64_t)(pixels / 8)};
        const cuuint64_t strides[3] = {C * 2, 128, C * 2 * 8};
        const cuuint32_t box_x[4]   = {64, 8, 6, TP / 8};
        const cuuint32_t box_o[4]   = {64, 8, 3, TP / 8};
        encode_map(encode, &tm_x, x, 4, dims, strides, box_x);
        encode_map(encode, &tm_o, d_out, 4, dims, strides, box_o);
        const cuuint64_t pdims[2]    = {64, (cuuint64_t)pixels * 6};
        const cuuint64_t pstrides[1] = {128};
        const cuuint32_t pbox[2]     = {64, STAGE_BYTES / 128};
        encode_map(encode, &tm_p, x, 2, pdims, pstrides, pbox);
        const cuuint64_t wdims[3]    = {C, 192, 2};
        const cuuint64_t wstrides[2] = {C * 2, C * 2 * 192};
        const cuuint32_t wbox[3]     = {64, 192, 2};
        encode_map(encode, &tm_w, w, 3, wdims, wstrides, wbox);
    }
    const int num_units = pixels / (TP * UNIT);
    const int nclusters = max_clusters * NSTATIC <= num_units ? max_clusters : num_units / NSTATIC;
    conv1x1_kernel<<<2 * nclusters, NTHREADS, SMEM_TOTAL, cudaStreamPerThread>>>(x, w, b, num_units, tm_x, tm_w, tm_o, tm_p);
}
```

```cpp
#include <cuda_runtime.h>
#include <cuda_bf16.h>
#include <cuda.h>
#include <stdint.h>

#define TUNE(name, value) constexpr int name = value
TUNE(RAMP_Q, 11);
TUNE(RAMP_0, -15);
TUNE(KSTART, 27);
TUNE(KRAMP, 4);
TUNE(EARLY_N, 4);
TUNE(EARLY_T, 415);
TUNE(EARLY_DT, 335);
TUNE(RA_T0, 1750);
TUNE(RA_DT, 460);
TUNE(RA_LEAD, 39);
TUNE(RA_FADE, 9);
TUNE(RA_END, 65);
TUNE(RA_MIN, 8);
TUNE(SHALLOW, 13);
TUNE(DRAIN_T0, 600);
TUNE(DRAIN_END, 11180);
TUNE(DRAIN_DT, 470);
TUNE(DRAIN_PRE, 1);

namespace {

constexpr int C           = 384;
constexpr int TP          = 32;
constexpr int UNIT        = 2;
constexpr int NSTATIC     = 4;
constexpr int KREG        = 5;
constexpr int HANDOVER    = 18;
constexpr int STAGES      = 4;
constexpr int NBUF        = 10;
constexpr int NLOCAL      = 2;
constexpr int STAGE_BYTES = TP * C * 2;
constexpr int OUT_BYTES   = TP * 192 * 2;
constexpr int SLAB_BYTES  = C * 64 * 2;
constexpr int SMEM_OUT    = STAGES * STAGE_BYTES;
constexpr int SMEM_BAR    = SMEM_OUT + NBUF * OUT_BYTES;
constexpr int SMEM_TOTAL  = SMEM_BAR + 512 + 1024;
constexpr int NTHREADS    = 512;
constexpr int SMEM_W      = SMEM_BAR - 3 * SLAB_BYTES;
constexpr int FREE_STAGES = SMEM_W / STAGE_BYTES;
static_assert(SMEM_W % 1024 == 0 && NLOCAL <= FREE_STAGES && FREE_STAGES < NSTATIC * UNIT, "layout");
static_assert(STAGES == 4 && NSTATIC * UNIT >= STAGES, "the shallow mode of the loader assumes four stages");
static_assert(SMEM_TOTAL <= 232448, "too much shared memory");

__device__ unsigned int g_sched;
__device__ unsigned long long g_dry;
__device__ unsigned int g_seen;

__device__ __forceinline__ uint32_t smem_u32(const void* p) { return (uint32_t)__cvta_generic_to_shared(p); }
__device__ __forceinline__ uint32_t now_ns() {
    uint32_t t;
    asm volatile("mov.u32 %0, %%globaltimer_lo;" : "=r"(t));
    return t;
}
__device__ __forceinline__ unsigned long long now_ns64() {
    unsigned long long t;
    asm volatile("mov.u64 %0, %%globaltimer;" : "=l"(t));
    return t;
}
__device__ __forceinline__ int lds(uint32_t addr) {
    int v;
    asm volatile("ld.volatile.shared.b32 %0, [%1];" : "=r"(v) : "r"(addr) : "memory");
    return v;
}
__device__ __forceinline__ void sts(uint32_t addr, int v) {
    asm volatile("st.volatile.shared.b32 [%0], %1;" ::"r"(addr), "r"(v) : "memory");
}
__device__ __forceinline__ void sts_cluster(uint32_t cluster_addr, int v) {
    asm volatile("st.volatile.shared::cluster.b32 [%0], %1;" ::"r"(cluster_addr), "r"(v) : "memory");
}
__device__ __forceinline__ void mbar_init(uint32_t bar, uint32_t count) {
    asm volatile("mbarrier.init.shared::cta.b64 [%0], %1;" ::"r"(bar), "r"(count) : "memory");
}
__device__ __forceinline__ void mbar_expect_tx(uint32_t bar, uint32_t bytes) {
    asm volatile("mbarrier.arrive.expect_tx.shared::cta.b64 _, [%0], %1;" ::"r"(bar), "r"(bytes) : "memory");
}
__device__ __forceinline__ void mbar_arrive(uint32_t bar) {
    asm volatile("mbarrier.arrive.shared::cta.b64 _, [%0];" ::"r"(bar) : "memory");
}
__device__ __forceinline__ void mbar_arrive_cluster(uint32_t cluster_addr) {
    asm volatile("mbarrier.arrive.shared::cluster.b64 _, [%0];" ::"r"(cluster_addr) : "memory");
}
__device__ __forceinline__ bool mbar_try(uint32_t bar, uint32_t parity) {
    uint32_t ok;
    asm volatile("{\n.reg .pred p;\nmbarrier.try_wait.parity.shared::cta.b64 p, [%1], %2;\nselp.u32 %0, 1, 0, p;\n}"
                 : "=r"(ok) : "r"(bar), "r"(parity) : "memory");
    return ok;
}
__device__ __forceinline__ bool mbar_test(uint32_t bar, uint32_t parity) {
    uint32_t ok;
    asm volatile("{\n.reg .pred p;\nmbarrier.test_wait.parity.shared::cta.b64 p, [%1], %2;\nselp.u32 %0, 1, 0, p;\n}"
                 : "=r"(ok) : "r"(bar), "r"(parity) : "memory");
    return ok;
}
__device__ __forceinline__ void mbar_wait(uint32_t bar, uint32_t parity) {
    asm volatile("{\n.reg .pred p, q;\n.reg .u32 n;\n"
                 "mbarrier.try_wait.parity.shared::cta.b64 p, [%0], %1;\n@p bra DONE;\nmov.u32 n, 0;\n"
                 "AGAIN:\nmbarrier.try_wait.parity.shared::cta.b64 p, [%0], %1;\nadd.u32 n, n, 1;\n"
                 "setp.lt.and.u32 q, n, 0x400000, !p;\n@q bra AGAIN;\nDONE:\n}"
                 ::"r"(bar), "r"(parity) : "memory");
}
__device__ __forceinline__ uint32_t mapa(uint32_t addr, uint32_t rank) {
    uint32_t r;
    asm("mapa.shared::cluster.u32 %0, %1, %2;" : "=r"(r) : "r"(addr), "r"(rank));
    return r;
}
__device__ __forceinline__ void fence_async_smem() { asm volatile("fence.proxy.async.shared::cta;" ::: "memory"); }
__device__ __forceinline__ void post_tile(uint32_t bar, uint32_t slot, uint32_t bytes, int value) {
    asm volatile("mbarrier.arrive.expect_tx.shared::cluster.b64 _, [%0], %1;" ::"r"(bar), "r"(bytes) : "memory");
    asm volatile("st.async.weak.shared::cluster.mbarrier::complete_tx::bytes.b32 [%0], %1, [%2];"
                 ::"r"(slot), "r"(value), "r"(bar) : "memory");
}
__device__ __forceinline__ void tma_load_w(uint32_t dst, const CUtensorMap* tm, int ch, uint32_t bar) {
    asm volatile("cp.async.bulk.tensor.3d.shared::cluster.global.mbarrier::complete_tx::bytes [%0], [%1, {%3, %4, %4}], [%2];"
                 ::"r"(dst), "l"(tm), "r"(bar), "r"(ch), "r"(0) : "memory");
}
__device__ __forceinline__ void tma_load_x(uint32_t dst, const CUtensorMap* tm, int tile, uint32_t bar) {
    asm volatile("cp.async.bulk.tensor.4d.shared::cluster.global.mbarrier::complete_tx::bytes"
                 " [%0], [%1, {%4, %4, %4, %3}], [%2];"
                 ::"r"(dst), "l"(tm), "r"(bar), "r"(tile * (TP / 8)), "r"(0) : "memory");
}
__device__ __forceinline__ void tma_load_x_multicast(uint32_t dst, const CUtensorMap* tm, int tile, uint32_t bar) {
    asm volatile("cp.async.bulk.tensor.4d.shared::cluster.global.mbarrier::complete_tx::bytes.multicast::cluster"
                 " [%0], [%1, {%4, %4, %4, %3}], [%2], %5;"
                 ::"r"(dst), "l"(tm), "r"(bar), "r"(tile * (TP / 8)), "r"(0), "h"((uint16_t)3) : "memory");
}
__device__ __forceinline__ void tma_store_out(const CUtensorMap* tm, uint32_t src, int slab, int tile) {
    asm volatile("cp.async.bulk.tensor.4d.global.shared::cta.bulk_group [%0, {%4, %4, %2, %3}], [%1];"
                 ::"l"(tm), "r"(src), "r"(slab), "r"(tile * (TP / 8)), "r"(0) : "memory");
    asm volatile("cp.async.bulk.commit_group;" ::: "memory");
}
__device__ __forceinline__ void l2_prefetch_tile(const CUtensorMap* tm, int tile) {
    asm volatile("cp.async.bulk.prefetch.tensor.2d.L2.global.tile [%0, {%1, %2}];"
                 ::"l"(tm), "r"(0), "r"(tile * (STAGE_BYTES / 128)) : "memory");
}

__device__ __forceinline__ void wgmma_rs(float (&d)[16], const uint32_t (&a)[4], uint64_t desc, int scale_d) {
    asm volatile(
        "{\n.reg .pred p;\nsetp.ne.b32 p, %21, 0;\n"
        "wgmma.mma_async.sync.aligned.m64n32k16.f32.bf16.bf16 "
        "{%0,%1,%2,%3,%4,%5,%6,%7,%8,%9,%10,%11,%12,%13,%14,%15},"
        "{%16,%17,%18,%19}, %20, p, 1, 1, 0;\n}"
        : "+f"(d[0]), "+f"(d[1]), "+f"(d[2]), "+f"(d[3]), "+f"(d[4]), "+f"(d[5]), "+f"(d[6]), "+f"(d[7]),
          "+f"(d[8]), "+f"(d[9]), "+f"(d[10]), "+f"(d[11]), "+f"(d[12]), "+f"(d[13]), "+f"(d[14]), "+f"(d[15])
        : "r"(a[0]), "r"(a[1]), "r"(a[2]), "r"(a[3]), "l"(desc), "r"(scale_d));
}
template <bool HI>
__device__ __forceinline__ uint32_t cvt_add_bias(float lo, float hi, uint32_t bias2) {
    uint32_t r;
    if (HI) asm("{\n.reg .b32 t, b;\n.reg .b16 l, h;\ncvt.rn.bf16x2.f32 t, %2, %1;\nmov.b32 {l, h}, %3;\nmov.b32 b, {h, h};\n"
                "add.rn.bf16x2 %0, t, b;\n}" : "=r"(r) : "f"(lo), "f"(hi), "r"(bias2));
    else asm("{\n.reg .b32 t, b;\n.reg .b16 l, h;\ncvt.rn.bf16x2.f32 t, %2, %1;\nmov.b32 {l, h}, %3;\nmov.b32 b, {l, l};\n"
             "add.rn.bf16x2 %0, t, b;\n}" : "=r"(r) : "f"(lo), "f"(hi), "r"(bias2));
    return r;
}

__global__ void __cluster_dims__(2, 1, 1) __launch_bounds__(NTHREADS, 1)
conv1x1_kernel(const __nv_bfloat16* __restrict__ x, const __nv_bfloat16* __restrict__ w,
               const __nv_bfloat16* __restrict__ bias, int num_units,
               const __grid_constant__ CUtensorMap tm_x, const __grid_constant__ CUtensorMap tm_w,
               const __grid_constant__ CUtensorMap tm_o, const __grid_constant__ CUtensorMap tm_p) {
    extern __shared__ uint8_t smem_raw[];
    const uint32_t smem = (smem_u32(smem_raw) + 1023u) & ~1023u;
    const uint32_t bar_full   = smem + SMEM_BAR;
    const uint32_t bar_empty  = bar_full + 8 * STAGES;
    const uint32_t bar_ofull  = bar_empty + 8 * STAGES;
    const uint32_t bar_oempty = bar_ofull + 8 * NBUF;
    const uint32_t bar_w      = bar_oempty + 8 * NBUF;
    const uint32_t bar_wfree  = bar_w + 24;
    const uint32_t bar_wloc   = bar_wfree + 8;
    const uint32_t bar_spare  = bar_wloc + 8;
    const uint32_t progress   = bar_spare + 16;
    const uint32_t total_slot = progress + 4;
    const uint32_t dry_slot   = progress + 8;
    const uint32_t zero_slot  = progress + 12;
    const uint32_t tile_slot  = progress + 16;

    const int tid = threadIdx.x;
    const int wg  = tid >> 7;
    uint32_t rank;
    asm("mov.u32 %0, %%cluster_ctarank;" : "=r"(rank));
    const int cluster_id = blockIdx.x >> 1;
    const int nclusters  = gridDim.x >> 1;
    const int ntiles     = num_units * UNIT;
    auto even_tile = [&](int j) { return (cluster_id + j / UNIT * nclusters) * UNIT + j % UNIT; };

    asm volatile("setmaxnreg.dec.sync.aligned.u32 32;");

    auto prefetch_lines = [&](const void* base, int bytes) {
        const char* p = static_cast<const char*>(base) + (tid & 31) * 128;
#pragma unroll
        for (int o = 0; o < bytes; o += 4096)
            if (o + 4096 <= bytes || (tid & 31) * 128 < bytes - o)
                asm volatile("prefetch.global.L2 [%0];" ::"l"(p + o) : "memory");
    };
    auto prefetch_half_tile = [&](int j) {
        prefetch_lines(x + (size_t)(even_tile(j) * TP + rank * (TP / 2)) * C, STAGE_BYTES / 2);
    };
    uint32_t t_entry = 0;
    if ((tid >> 5) == 14) {
        prefetch_lines(w + (blockIdx.x & 63) * (C * C / 64), C * C * 2 / 64);
        t_entry = now_ns();
        prefetch_half_tile(0);
        if (tid == 448) asm volatile("prefetch.tensormap [%0];" ::"l"(&tm_p) : "memory");
    }
    if (tid == 384) {
        asm volatile("prefetch.tensormap [%0];" ::"l"(&tm_w) : "memory");
        asm volatile("prefetch.tensormap [%0];" ::"l"(&tm_x) : "memory");
        for (int g = 0; g < 3; g++) mbar_init(bar_w + 8 * g, 1);
        for (int s = 0; s < NLOCAL; s++) mbar_init(bar_full + 8 * s, 1);
        asm volatile("fence.mbarrier_init.release.cluster;" ::: "memory");
        fence_async_smem();
        for (int g = 0; g < 3; g++) {
            mbar_expect_tx(bar_w + 8 * g, SLAB_BYTES);
            tma_load_w(smem + SMEM_W + g * SLAB_BYTES, &tm_w, rank * 192 + g * 64, bar_w + 8 * g);
        }
        for (int s = 0; s < NLOCAL; s++) {
            sts(tile_slot + 4 * s, even_tile(s));
            mbar_expect_tx(bar_full + 8 * s, STAGE_BYTES);
            tma_load_x(smem + s * STAGE_BYTES, &tm_x, even_tile(s), bar_full + 8 * s);
        }
    }
    if (tid == 416) {
        for (int s = NLOCAL; s < STAGES; s++) mbar_init(bar_full + 8 * s, 1);
        for (int s = 0; s < STAGES; s++) mbar_init(bar_empty + 8 * s, 24);
        for (int s = 0; s < NBUF; s++) {
            mbar_init(bar_ofull + 8 * s, 12);
            mbar_init(bar_oempty + 8 * s, 1);
        }
        mbar_init(bar_wfree, 24);
        mbar_init(bar_wloc, 12);
        mbar_init(bar_spare, 1);
        mbar_init(bar_spare + 8, 1);
        sts(progress, 0);
        sts(total_slot, 0);
        sts(dry_slot, 0);
        sts(zero_slot, 0);
        asm volatile("fence.mbarrier_init.release.cluster;" ::: "memory");
        fence_async_smem();
        asm volatile("prefetch.tensormap [%0];" ::"l"(&tm_o) : "memory");
    }
    __syncwarp();
    asm volatile("barrier.cluster.arrive.relaxed.aligned;" ::: "memory");

    if (wg == 3) {
        if ((tid >> 5) == 14) {
            uint32_t due = EARLY_T;
#pragma unroll 1
            for (int j = 1; j < EARLY_N; j++, due += EARLY_DT) {
                while (now_ns() - t_entry < due) {}
                prefetch_half_tile(j);
            }
        }
        __syncwarp();
        asm volatile("barrier.cluster.wait.aligned;" ::: "memory");
        if (tid == 384 && rank == 0) {
            const uint32_t peer = mapa(smem, 1) - smem;
            const int shallow = max(ntiles - SHALLOW * nclusters, NSTATIC * UNIT * nclusters);
            int s = NLOCAL, n = 0;
            uint32_t ph = 1;
            int unit = cluster_id;
            for (int u = 0; unit < num_units; u++) {
                const bool late = unit * UNIT >= ntiles - 6 * nclusters;
                const unsigned long long t_fetch = late ? now_ns64() : 0;
                int next = unit - (NSTATIC - 1) * nclusters;
                if (u >= NSTATIC - 1) next = (int)atomicInc(&g_sched, (unsigned)(num_units - (NSTATIC - 1) * nclusters - 1));
#pragma unroll 1
                for (int h = 0; h < UNIT; h++, n++) {
                    if (n < NLOCAL) continue;
                    const int tile = unit * UNIT + h;
                    if (n == FREE_STAGES) mbar_wait(bar_wfree, 0);
                    mbar_wait(bar_empty + 8 * s, ph);
                    if (tile >= shallow) mbar_wait(bar_empty + 8 * ((s + 1) & 3), s == 3 ? ph ^ 1 : ph);
                    const uint32_t bar = bar_full + 8 * s;
                    tma_load_x_multicast(smem + s * STAGE_BYTES, &tm_x, tile, bar);
                    post_tile(bar, tile_slot + 4 * (n & 31), STAGE_BYTES + 4, tile);
                    post_tile(bar + peer, tile_slot + 4 * (n & 31) + peer, STAGE_BYTES + 4, tile);
                    sts_cluster(progress + peer, unit * UNIT + h * nclusters);
                    if (++s == STAGES) { s = 0; ph ^= 1; }
                    if (late && h == 0) {
                        asm volatile("" : "+r"(next)::"memory");
                        const int succ = next + NSTATIC * nclusters;
                        if (succ >= num_units) {
                            sts(total_slot, n + UNIT);
                            sts_cluster(total_slot + peer, n + UNIT);
                        }
                        if (succ == num_units - 1)
                            asm volatile("st.relaxed.gpu.global.b64 [%0], %1;" ::"l"(&g_dry), "l"(t_fetch) : "memory");
                    }
                }
                asm volatile("" : "+r"(next)::"memory");
                unit = next + NSTATIC * nclusters;
            }
            sts(total_slot, n);
            sts_cluster(total_slot + peer, n);
            sts_cluster(progress + peer, 0x7fffffff);
            mbar_wait(bar_empty + 8 * s, ph);
            post_tile(bar_full + 8 * s, tile_slot + 4 * (n & 31), 4, -1);
            post_tile(bar_full + 8 * s + peer, tile_slot + 4 * (n & 31) + peer, 4, -1);
#pragma unroll 1
            for (int e = 1; e < STAGES; e++) {
                if (++s == STAGES) { s = 0; ph ^= 1; }
                mbar_wait(bar_empty + 8 * s, ph);
            }
        } else if (tid == 448 && rank == 1) {
            auto wait_loader = [&](int tile, uint32_t unless) {
                while (lds(progress) < tile && lds(unless) == 0 && now_ns() - t_entry < 1000000000u) __nanosleep(64);
            };
            const int slope = (RA_LEAD - RA_MIN) * 256 / (RA_END - RA_FADE);
            int lead = RA_LEAD * 256;
            uint32_t due = RA_T0;
#pragma unroll 1
            for (int j = EARLY_N; j / UNIT * nclusters < num_units; j++, due += RA_DT) {
                const int t = even_tile(j);
                if (j >= RA_FADE && j < RA_END) lead -= slope;
                wait_loader(cluster_id * UNIT + j * nclusters - (lead * nclusters >> 10), dry_slot);
                while (now_ns() - t_entry < due) {}
                if (t < ntiles) l2_prefetch_tile(&tm_p, t);
            }
            wait_loader(0x7fffffff, zero_slot);
        } else if (tid == 384 || tid == 448) {
            const unsigned long long t_start = now_ns64();
            for (uint32_t it = 0; it < (1u << 22); it++) {
                unsigned long long v;
                asm volatile("ld.relaxed.gpu.global.b64 %0, [%1];" : "=l"(v) : "l"(&g_dry) : "memory");
                if (v > t_start) { sts(dry_slot, (uint32_t)v | 1); break; }
                if (lds(dry_slot)) break;
                __nanosleep(200);
            }
            if (atomicInc(&g_seen, gridDim.x - 1) == gridDim.x - 1)
                asm volatile("st.relaxed.gpu.global.b64 [%0], %1;" ::"l"(&g_dry), "l"(0ull) : "memory");
        } else if ((tid & 63) == 32) {
            uint32_t base = smem;
            asm volatile("" : "+r"(base));
            const uint32_t ofull = base + (bar_ofull - smem), otile = base + (tile_slot - smem);
            const uint32_t total_at = base + (total_slot - smem);
            int k = (tid >> 6) & 1;
            auto wait_filled = [&](int j) -> bool {
                const uint32_t lap = (uint32_t)j / NBUF, bar = ofull + 8 * (j - lap * NBUF);
                for (uint32_t it = 0; it < (1u << 22); it++) {
                    if (mbar_try(bar, lap & 1)) return true;
                    const int total = lds(total_at);
                    if (total != 0 && j >= total) break;
                }
                return false;
            };
            auto test_filled = [&](int j) -> bool {
                const uint32_t lap = (uint32_t)j / NBUF;
                return mbar_test(ofull + 8 * (j - lap * NBUF), lap & 1);
            };
            const int skew = cluster_id & 1;
            auto trigger = [&]() -> int { return k + min(max(0, RAMP_0 + (k + skew) * RAMP_Q) >> 4, NBUF - 1); };
            auto store = [&]() -> int {
                const int tile = lds(otile + 4 * (k & 31));
                const uint32_t slot = (uint32_t)k % NBUF;
                tma_store_out(&tm_o, base + SMEM_OUT + slot * OUT_BYTES, rank * 3, tile);
                asm volatile("cp.async.bulk.wait_group.read 0;" ::: "memory");
                mbar_arrive(ofull + 8 * (NBUF + slot));
                k += 2;
                return tile;
            };
            const int near_end = ntiles - (KREG + 2 * NBUF) * nclusters;
            while (wait_filled(trigger()))
                if (store() >= near_end) break;
            uint32_t t_dry = 0, due = 0;
            for (uint32_t it = 0; it < (1u << 22); it++) {
                int total = lds(total_at);
                const int m = trigger();
                if ((total == 0 || m < total) && test_filled(m)) { store(); continue; }
                t_dry = lds(base + (dry_slot - smem));
                if (t_dry) {
                    if (total == 0) total = m + KREG + STAGES + DRAIN_PRE;
                    due = t_dry + max(DRAIN_T0, DRAIN_END - (total - k) * DRAIN_DT);
                    if ((int)(now_ns() - due) >= 0) break;
                } else if (total != 0 && total <= m + 1 && test_filled(total - 1)) {
                    break;
                }
            }
            if (!t_dry) {
                due = now_ns();
                t_dry = (due - DRAIN_END) | 1;
                sts(base + (dry_slot - smem), t_dry);
            }
            uint32_t prev = base + (bar_spare - smem) + 8 * (k & 1);
            while (true) {
                const int total = lds(total_at);
                if (total != 0) {
                    if (k >= total) break;
                    due = t_dry + DRAIN_END - (total - k) * DRAIN_DT;
                }
                if (!wait_filled(k)) break;
                const int tile = lds(otile + 4 * (k & 31));
                const uint32_t slot = (uint32_t)k % NBUF;
                while ((int)(now_ns() - due) < 0) {}
                tma_store_out(&tm_o, base + SMEM_OUT + slot * OUT_BYTES, rank * 3, tile);
                asm volatile("cp.async.bulk.wait_group.read 1;" ::: "memory");
                mbar_arrive(prev);
                prev = ofull + 8 * (NBUF + slot);
                k += 2;
                due += 2 * DRAIN_DT;
            }
            asm volatile("cp.async.bulk.wait_group.read 0;" ::: "memory");
        }
    } else {
        asm volatile("setmaxnreg.inc.sync.aligned.u32 160;");
        const int lane = tid & 31;
        const int warp = (tid >> 5) & 3;
        if (wg == 2) asm volatile("bar.arrive 8, 256;" ::: "memory");

        uint32_t bias2;
        {
            const unsigned short* bp =
                reinterpret_cast<const unsigned short*>(bias) + rank * 192 + wg * 64 + warp * 16 + (lane >> 2);
            const uint32_t b0 = bp[0], b1 = bp[8];
            bias2 = b0 | (b1 << 16);
        }
        const uint32_t swz = (uint32_t)(((warp * 2 + ((lane >> 3) & 1)) ^ (lane & 7)) << 4);
        const uint32_t lead = mapa(smem, 0) - smem;

        uint32_t a[24][4];
        asm volatile("barrier.cluster.wait.aligned;" ::: "memory");
        mbar_wait(bar_w + 8 * wg, 0);
        {
            const uint32_t base = smem + SMEM_W + wg * SLAB_BYTES + ((lane >> 4) * 8 + (lane & 7)) * 128 + swz;
#pragma unroll
            for (int ks = 0; ks < 24; ks++)
                asm volatile("ldmatrix.sync.aligned.m8n8.x4.trans.shared.b16 {%0,%1,%2,%3}, [%4];"
                             : "=r"(a[ks][0]), "=r"(a[ks][1]), "=r"(a[ks][2]), "=r"(a[ks][3])
                             : "r"(base + ks * 2048) : "memory");
        }
        fence_async_smem();
        __syncwarp();
        if (lane == 0) {
            mbar_arrive_cluster(bar_wfree + lead);
            mbar_arrive(bar_wloc);
        }

        uint32_t st_base = smem + SMEM_OUT + wg * 1024 + (lane >> 4) * 3072 + (lane & 7) * 128 + swz;
        const int wgu = __shfl_sync(0xffffffffu, wg, 0);
        asm volatile("" : "+r"(st_base), "+r"(bias2));
        const uint64_t desc0 = (uint64_t)((smem & 0x3FFFF) >> 4) | (1ull << 16) | ((6144ull >> 4) << 32) | (1ull << 62);

        int s = 0, ob = 0, i = 0;
        uint32_t ph = 0, oph = 1;
        float d[16];
        uint32_t q[KREG][8];
        auto compute = [&]() -> bool {
            mbar_wait(bar_full + 8 * s, ph);
            if (lds(tile_slot + 4 * (i & 31)) < 0) return false;
            const uint64_t desc = desc0 + (uint64_t)(s * (STAGE_BYTES >> 4));
            asm volatile("bar.sync %0, 256;" ::"r"(8 + wgu) : "memory");
            asm volatile("wgmma.fence.sync.aligned;" ::: "memory");
#pragma unroll
            for (int ks = 0; ks < 24; ks++) {
                wgmma_rs(d, a[ks], desc + (uint64_t)(((ks >> 2) * 1024 + (ks & 3) * 32) >> 4), ks != 0);
                if (ks == HANDOVER - 1) asm volatile("bar.arrive %0, 256;" ::"r"(wgu == 2 ? 8 : 9 + wgu) : "memory");
            }
            asm volatile("wgmma.commit_group.sync.aligned;" ::: "memory");
            asm volatile("wgmma.wait_group.sync.aligned 0;" ::: "memory");
#pragma unroll
            for (int j = 0; j < 16; j++) asm volatile("" : "+f"(d[j])::"memory");
            if (lane == 0) mbar_arrive_cluster(bar_empty + 8 * s + lead);
            if (++s == STAGES) { s = 0; ph ^= 1; }
            return true;
        };
        auto pack = [&](uint32_t (&p)[8]) {
#pragma unroll
            for (int j = 0; j < 8; j += 2) {
                p[j]     = cvt_add_bias<false>(d[2 * j], d[2 * j + 1], bias2);
                p[j + 1] = cvt_add_bias<true>(d[2 * j + 2], d[2 * j + 3], bias2);
            }
        };
        auto put = [&](uint32_t st, const uint32_t (&p)[8]) {
#pragma unroll
            for (int j = 0; j < 2; j++)
                asm volatile("stmatrix.sync.aligned.m8n8.x4.trans.shared.b16 [%0], {%1,%2,%3,%4};"
                             ::"r"(st + j * 6144), "r"(p[4 * j]), "r"(p[4 * j + 1]), "r"(p[4 * j + 2]), "r"(p[4 * j + 3])
                             : "memory");
        };
        auto acquire = [&]() -> uint32_t {
            mbar_wait(bar_oempty + 8 * ob, oph);
            return st_base + ob * OUT_BYTES;
        };
        auto publish = [&]() {
            fence_async_smem();
            __syncwarp();
            if (lane == 0) mbar_arrive(bar_ofull + 8 * ob);
            if (++ob == NBUF) { ob = 0; oph ^= 1; }
        };

        const int kstart = KSTART - cluster_id % KRAMP;
        int held = 0, h = 0;
        bool more = true;
#pragma unroll 1
        for (; i < kstart; i++) {
            more = compute();
            if (!more) break;
            pack(q[0]);
            if (i == 0) mbar_wait(bar_wloc, 0);
            put(acquire(), q[0]);
            publish();
        }
        if (more) {
            int kstep = kstart;
#pragma unroll 1
            for (; compute(); i++) {
                if (h == 0 && i >= kstep) {
#pragma unroll
                    for (int k = 0; k < KREG; k++)
                        if (held == k) pack(q[k]);
                    kstep = ++held == KREG ? 0x7fffffff : kstep + KRAMP;
                    continue;
                }
                const uint32_t st = acquire();
#pragma unroll
                for (int k = 0; k < KREG; k++)
                    if (h == k) { put(st, q[k]); pack(q[k]); }
                publish();
                if (++h == held) h = 0;
            }
#pragma unroll 1
            for (int left = held; left > 0; left--) {
                const uint32_t st = acquire();
#pragma unroll
                for (int k = 0; k < KREG; k++)
                    if (h == k) put(st, q[k]);
                publish();
                if (++h == held) h = 0;
            }
        }
        if (wg == 0) asm volatile("bar.sync 8, 256;" ::: "memory");
    }
}

typedef CUresult (*EncodeTiledFn)(CUtensorMap*, CUtensorMapDataType, cuuint32_t, void*, const cuuint64_t*,
                                  const cuuint64_t*, const cuuint32_t*, const cuuint32_t*, CUtensorMapInterleave,
                                  CUtensorMapSwizzle, CUtensorMapL2promotion, CUtensorMapFloatOOBfill);

void encode_map(EncodeTiledFn fn, CUtensorMap* tm, const void* ptr, int rank, const cuuint64_t* dims,
                const cuuint64_t* strides, const cuuint32_t* box) {
    const cuuint32_t estr[4] = {1, 1, 1, 1};
    fn(tm, CU_TENSOR_MAP_DATA_TYPE_BFLOAT16, rank, const_cast<void*>(ptr), dims, strides, box, estr,
       CU_TENSOR_MAP_INTERLEAVE_NONE, CU_TENSOR_MAP_SWIZZLE_128B, CU_TENSOR_MAP_L2_PROMOTION_L2_128B,
       CU_TENSOR_MAP_FLOAT_OOB_FILL_NONE);
}

}

extern "C" void kernel_launch(void* const* d_in, const int* in_sizes, int n_in, void* d_out, int out_size) {
    const __nv_bfloat16* x = (const __nv_bfloat16*)d_in[0];
    const __nv_bfloat16* w = (const __nv_bfloat16*)d_in[1];
    const __nv_bfloat16* b = (const __nv_bfloat16*)d_in[2];
    const int pixels = in_sizes[0] / C;

    static EncodeTiledFn encode = nullptr;
    static int max_clusters = 0;
    if (!encode) {
        void* fn = nullptr;
        cudaDriverEntryPointQueryResult qr;
        cudaGetDriverEntryPoint("cuTensorMapEncodeTiled", &fn, cudaEnableDefault, &qr);
        encode = (EncodeTiledFn)fn;
        cudaFuncSetAttribute(conv1x1_kernel, cudaFuncAttributeMaxDynamicSharedMemorySize, SMEM_TOTAL);
        cudaLaunchConfig_t cfg = {};
        cfg.gridDim = dim3(2, 1, 1);
        cfg.blockDim = dim3(NTHREADS, 1, 1);
        cfg.dynamicSmemBytes = SMEM_TOTAL;
        cudaLaunchAttribute at[1];
        at[0].id = cudaLaunchAttributeClusterDimension;
        at[0].val.clusterDim.x = 2; at[0].val.clusterDim.y = 1; at[0].val.clusterDim.z = 1;
        cfg.attrs = at; cfg.numAttrs = 1;
        if (cudaOccupancyMaxActiveClusters(&max_clusters, conv1x1_kernel, &cfg) != cudaSuccess || max_clusters <= 0) {
            (void)cudaGetLastError();
            int dev = 0, sms = 0;
            cudaGetDevice(&dev);
            cudaDeviceGetAttribute(&sms, cudaDevAttrMultiProcessorCount, dev);
            max_clusters = sms / 2;
        }
    }
    CUtensorMap tm_x, tm_w, tm_o, tm_p;
    {
        const cuuint64_t dims[4]    = {64, 8, 6, (cuuint64_t)(pixels / 8)};
        const cuuint64_t strides[3] = {C * 2, 128, C * 2 * 8};
        const cuuint32_t box_x[4]   = {64, 8, 6, TP / 8};
        const cuuint32_t box_o[4]   = {64, 8, 3, TP / 8};
        encode_map(encode, &tm_x, x, 4, dims, strides, box_x);
        encode_map(encode, &tm_o, d_out, 4, dims, strides, box_o);
        const cuuint64_t pdims[2]    = {64, (cuuint64_t)pixels * 6};
        const cuuint64_t pstrides[1] = {128};
        const cuuint32_t pbox[2]     = {64, STAGE_BYTES / 128};
        encode_map(encode, &tm_p, x, 2, pdims, pstrides, pbox);
        const cuuint64_t wdims[3]    = {C, 192, 2};
        const cuuint64_t wstrides[2] = {C * 2, C * 2 * 192};
        const cuuint32_t wbox[3]     = {64, 192, 2};
        encode_map(encode, &tm_w, w, 3, wdims, wstrides, wbox);
    }
    const int num_units = pixels / (TP * UNIT);
    const int nclusters = max_clusters * NSTATIC <= num_units ? max_clusters : num_units / NSTATIC;
    conv1x1_kernel<<<2 * nclusters, NTHREADS, SMEM_TOTAL, cudaStreamPerThread>>>(x, w, b, num_units, tm_x, tm_w, tm_o, tm_p);
}
```

```cpp
#include <cuda_runtime.h>
#include <cuda_bf16.h>
#include <cuda.h>
#include <stdint.h>

#define TUNE(name, value) constexpr int name = value
TUNE(RAMP_Q, 11);
TUNE(RAMP_0, -13);
TUNE(KSTART, 27);
TUNE(KRAMP, 4);
TUNE(EARLY_N, 4);
TUNE(EARLY_T, 370);
TUNE(EARLY_DT, 330);
TUNE(RA_T0, 1490);
TUNE(RA_DT, 468);
TUNE(RA_LEAD, 39);
TUNE(RA_FADE, 9);
TUNE(RA_END, 67);
TUNE(RA_MIN, 8);
TUNE(SHALLOW, 13);
TUNE(DRAIN_T0, 600);
TUNE(DRAIN_END, 11200);
TUNE(DRAIN_DT, 470);
TUNE(DRAIN_PRE, 1);

namespace {

constexpr int C           = 384;
constexpr int TP          = 32;
constexpr int UNIT        = 2;
constexpr int NSTATIC     = 4;
constexpr int KREG        = 5;
constexpr int HANDOVER    = 18;
constexpr int STAGES      = 4;
constexpr int NBUF        = 10;
constexpr int NLOCAL      = 2;
constexpr int STAGE_BYTES = TP * C * 2;
constexpr int OUT_BYTES   = TP * 192 * 2;
constexpr int CHUNK_BYTES = 64 * 192 * 2;
constexpr int W_AHEAD     = 4;
constexpr int SMEM_OUT    = STAGES * STAGE_BYTES;
constexpr int SMEM_BAR    = SMEM_OUT + NBUF * OUT_BYTES;
constexpr int SMEM_TOTAL  = SMEM_BAR + 512 + 1024;
constexpr int NTHREADS    = 512;
constexpr int SMEM_W      = SMEM_BAR - 6 * CHUNK_BYTES;
constexpr int FREE_STAGES = SMEM_W / STAGE_BYTES;
static_assert(SMEM_W % 1024 == 0 && NLOCAL <= FREE_STAGES && FREE_STAGES < NSTATIC * UNIT, "layout");
static_assert(STAGES == 4 && NSTATIC * UNIT >= STAGES, "the shallow mode of the loader assumes four stages");
static_assert(SMEM_TOTAL <= 232448, "too much shared memory");

__device__ unsigned int g_sched;
__device__ unsigned long long g_dry;
__device__ unsigned int g_seen;

__device__ __forceinline__ uint32_t smem_u32(const void* p) { return (uint32_t)__cvta_generic_to_shared(p); }
__device__ __forceinline__ uint32_t now_ns() {
    uint32_t t;
    asm volatile("mov.u32 %0, %%globaltimer_lo;" : "=r"(t));
    return t;
}
__device__ __forceinline__ unsigned long long now_ns64() {
    unsigned long long t;
    asm volatile("mov.u64 %0, %%globaltimer;" : "=l"(t));
    return t;
}
__device__ __forceinline__ int lds(uint32_t addr) {
    int v;
    asm volatile("ld.volatile.shared.b32 %0, [%1];" : "=r"(v) : "r"(addr) : "memory");
    return v;
}
__device__ __forceinline__ void sts(uint32_t addr, int v) {
    asm volatile("st.volatile.shared.b32 [%0], %1;" ::"r"(addr), "r"(v) : "memory");
}
__device__ __forceinline__ void sts_cluster(uint32_t cluster_addr, int v) {
    asm volatile("st.volatile.shared::cluster.b32 [%0], %1;" ::"r"(cluster_addr), "r"(v) : "memory");
}
__device__ __forceinline__ void mbar_init(uint32_t bar, uint32_t count) {
    asm volatile("mbarrier.init.shared::cta.b64 [%0], %1;" ::"r"(bar), "r"(count) : "memory");
}
__device__ __forceinline__ void mbar_expect_tx(uint32_t bar, uint32_t bytes) {
    asm volatile("mbarrier.arrive.expect_tx.shared::cta.b64 _, [%0], %1;" ::"r"(bar), "r"(bytes) : "memory");
}
__device__ __forceinline__ void mbar_arrive(uint32_t bar) {
    asm volatile("mbarrier.arrive.shared::cta.b64 _, [%0];" ::"r"(bar) : "memory");
}
__device__ __forceinline__ void mbar_arrive_cluster(uint32_t cluster_addr) {
    asm volatile("mbarrier.arrive.shared::cluster.b64 _, [%0];" ::"r"(cluster_addr) : "memory");
}
__device__ __forceinline__ bool mbar_try(uint32_t bar, uint32_t parity) {
    uint32_t ok;
    asm volatile("{\n.reg .pred p;\nmbarrier.try_wait.parity.shared::cta.b64 p, [%1], %2;\nselp.u32 %0, 1, 0, p;\n}"
                 : "=r"(ok) : "r"(bar), "r"(parity) : "memory");
    return ok;
}
__device__ __forceinline__ bool mbar_test(uint32_t bar, uint32_t parity) {
    uint32_t ok;
    asm volatile("{\n.reg .pred p;\nmbarrier.test_wait.parity.shared::cta.b64 p, [%1], %2;\nselp.u32 %0, 1, 0, p;\n}"
                 : "=r"(ok) : "r"(bar), "r"(parity) : "memory");
    return ok;
}
__device__ __forceinline__ void mbar_wait(uint32_t bar, uint32_t parity) {
    asm volatile("{\n.reg .pred p, q;\n.reg .u32 n;\n"
                 "mbarrier.try_wait.parity.shared::cta.b64 p, [%0], %1;\n@p bra DONE;\nmov.u32 n, 0;\n"
                 "AGAIN:\nmbarrier.try_wait.parity.shared::cta.b64 p, [%0], %1;\nadd.u32 n, n, 1;\n"
                 "setp.lt.and.u32 q, n, 0x400000, !p;\n@q bra AGAIN;\nDONE:\n}"
                 ::"r"(bar), "r"(parity) : "memory");
}
__device__ __forceinline__ uint32_t mapa(uint32_t addr, uint32_t rank) {
    uint32_t r;
    asm("mapa.shared::cluster.u32 %0, %1, %2;" : "=r"(r) : "r"(addr), "r"(rank));
    return r;
}
__device__ __forceinline__ void fence_async_smem() { asm volatile("fence.proxy.async.shared::cta;" ::: "memory"); }
__device__ __forceinline__ void post_tile(uint32_t bar, uint32_t slot, uint32_t bytes, int value) {
    asm volatile("mbarrier.arrive.expect_tx.shared::cluster.b64 _, [%0], %1;" ::"r"(bar), "r"(bytes) : "memory");
    asm volatile("st.async.weak.shared::cluster.mbarrier::complete_tx::bytes.b32 [%0], %1, [%2];"
                 ::"r"(slot), "r"(value), "r"(bar) : "memory");
}
__device__ __forceinline__ void tma_load_w(uint32_t dst, const CUtensorMap* tm, int k, int slab, uint32_t bar) {
    asm volatile("cp.async.bulk.tensor.3d.shared::cluster.global.mbarrier::complete_tx::bytes [%0], [%1, {%3, %4, %5}], [%2];"
                 ::"r"(dst), "l"(tm), "r"(bar), "r"(0), "r"(k), "r"(slab) : "memory");
}
__device__ __forceinline__ void tma_load_x(uint32_t dst, const CUtensorMap* tm, int tile, uint32_t bar) {
    asm volatile("cp.async.bulk.tensor.4d.shared::cluster.global.mbarrier::complete_tx::bytes"
                 " [%0], [%1, {%4, %4, %4, %3}], [%2];"
                 ::"r"(dst), "l"(tm), "r"(bar), "r"(tile * (TP / 8)), "r"(0) : "memory");
}
__device__ __forceinline__ void tma_load_x_multicast(uint32_t dst, const CUtensorMap* tm, int tile, uint32_t bar) {
    asm volatile("cp.async.bulk.tensor.4d.shared::cluster.global.mbarrier::complete_tx::bytes.multicast::cluster"
                 " [%0], [%1, {%4, %4, %4, %3}], [%2], %5;"
                 ::"r"(dst), "l"(tm), "r"(bar), "r"(tile * (TP / 8)), "r"(0), "h"((uint16_t)3) : "memory");
}
__device__ __forceinline__ void tma_store_out(const CUtensorMap* tm, uint32_t src, int slab, int tile) {
    asm volatile("cp.async.bulk.tensor.4d.global.shared::cta.bulk_group [%0, {%4, %4, %2, %3}], [%1];"
                 ::"l"(tm), "r"(src), "r"(slab), "r"(tile * (TP / 8)), "r"(0) : "memory");
    asm volatile("cp.async.bulk.commit_group;" ::: "memory");
}
__device__ __forceinline__ void l2_prefetch_tile(const CUtensorMap* tm, int tile) {
    asm volatile("cp.async.bulk.prefetch.tensor.2d.L2.global.tile [%0, {%1, %2}];"
                 ::"l"(tm), "r"(0), "r"(tile * (STAGE_BYTES / 128)) : "memory");
}

__device__ __forceinline__ void wgmma_rs(float (&d)[16], const uint32_t (&a)[4], uint64_t desc, int scale_d) {
    asm volatile(
        "{\n.reg .pred p;\nsetp.ne.b32 p, %21, 0;\n"
        "wgmma.mma_async.sync.aligned.m64n32k16.f32.bf16.bf16 "
        "{%0,%1,%2,%3,%4,%5,%6,%7,%8,%9,%10,%11,%12,%13,%14,%15},"
        "{%16,%17,%18,%19}, %20, p, 1, 1, 0;\n}"
        : "+f"(d[0]), "+f"(d[1]), "+f"(d[2]), "+f"(d[3]), "+f"(d[4]), "+f"(d[5]), "+f"(d[6]), "+f"(d[7]),
          "+f"(d[8]), "+f"(d[9]), "+f"(d[10]), "+f"(d[11]), "+f"(d[12]), "+f"(d[13]), "+f"(d[14]), "+f"(d[15])
        : "r"(a[0]), "r"(a[1]), "r"(a[2]), "r"(a[3]), "l"(desc), "r"(scale_d));
}
template <bool HI>
__device__ __forceinline__ uint32_t cvt_add_bias(float lo, float hi, uint32_t bias2) {
    uint32_t r;
    if (HI) asm("{\n.reg .b32 t, b;\n.reg .b16 l, h;\ncvt.rn.bf16x2.f32 t, %2, %1;\nmov.b32 {l, h}, %3;\nmov.b32 b, {h, h};\n"
                "add.rn.bf16x2 %0, t, b;\n}" : "=r"(r) : "f"(lo), "f"(hi), "r"(bias2));
    else asm("{\n.reg .b32 t, b;\n.reg .b16 l, h;\ncvt.rn.bf16x2.f32 t, %2, %1;\nmov.b32 {l, h}, %3;\nmov.b32 b, {l, l};\n"
             "add.rn.bf16x2 %0, t, b;\n}" : "=r"(r) : "f"(lo), "f"(hi), "r"(bias2));
    return r;
}

__global__ void __cluster_dims__(2, 1, 1) __launch_bounds__(NTHREADS, 1)
conv1x1_kernel(const __nv_bfloat16* __restrict__ x, const __nv_bfloat16* __restrict__ w,
               const __nv_bfloat16* __restrict__ bias, int num_units,
               const __grid_constant__ CUtensorMap tm_x, const __grid_constant__ CUtensorMap tm_w,
               const __grid_constant__ CUtensorMap tm_o, const __grid_constant__ CUtensorMap tm_p) {
    extern __shared__ uint8_t smem_raw[];
    const uint32_t smem = (smem_u32(smem_raw) + 1023u) & ~1023u;
    const uint32_t bar_full   = smem + SMEM_BAR;
    const uint32_t bar_empty  = bar_full + 8 * STAGES;
    const uint32_t bar_ofull  = bar_empty + 8 * STAGES;
    const uint32_t bar_oempty = bar_ofull + 8 * NBUF;
    const uint32_t bar_w      = bar_oempty + 8 * NBUF;
    const uint32_t bar_wfree  = bar_w + 48;
    const uint32_t bar_wloc   = bar_wfree + 8;
    const uint32_t bar_spare  = bar_wloc + 8;
    const uint32_t progress   = bar_spare + 16;
    const uint32_t total_slot = progress + 4;
    const uint32_t dry_slot   = progress + 8;
    const uint32_t zero_slot  = progress + 12;
    const uint32_t tile_slot  = progress + 16;

    const int tid = threadIdx.x;
    const int wg  = tid >> 7;
    uint32_t rank;
    asm("mov.u32 %0, %%cluster_ctarank;" : "=r"(rank));
    const int cluster_id = blockIdx.x >> 1;
    const int nclusters  = gridDim.x >> 1;
    const int ntiles     = num_units * UNIT;
    auto even_tile = [&](int j) { return (cluster_id + j / UNIT * nclusters) * UNIT + j % UNIT; };

    asm volatile("setmaxnreg.dec.sync.aligned.u32 32;");

    auto prefetch_lines = [&](const void* base, int bytes) {
        const char* p = static_cast<const char*>(base) + (tid & 31) * 128;
#pragma unroll
        for (int o = 0; o < bytes; o += 4096)
            if (o + 4096 <= bytes || (tid & 31) * 128 < bytes - o)
                asm volatile("prefetch.global.L2 [%0];" ::"l"(p + o) : "memory");
    };
    auto prefetch_half_tile = [&](int j) {
        prefetch_lines(x + (size_t)(even_tile(j) * TP + rank * (TP / 2)) * C, STAGE_BYTES / 2);
    };
    uint32_t t_entry = 0;
    if ((tid >> 5) == 14) {
        prefetch_lines(w + (blockIdx.x & 63) * (C * C / 64), C * C * 2 / 64);
        t_entry = now_ns();
        prefetch_half_tile(0);
        if (tid == 448) asm volatile("prefetch.tensormap [%0];" ::"l"(&tm_p) : "memory");
    }
    if (tid == 384) {
        asm volatile("prefetch.tensormap [%0];" ::"l"(&tm_w) : "memory");
        asm volatile("prefetch.tensormap [%0];" ::"l"(&tm_x) : "memory");
        for (int c = 0; c < 6; c++) mbar_init(bar_w + 8 * c, 1);
        for (int s = 0; s < NLOCAL; s++) mbar_init(bar_full + 8 * s, 1);
        asm volatile("fence.mbarrier_init.release.cluster;" ::: "memory");
        fence_async_smem();
        auto load_x = [&](int s) {
            sts(tile_slot + 4 * s, even_tile(s));
            mbar_expect_tx(bar_full + 8 * s, STAGE_BYTES);
            tma_load_x(smem + s * STAGE_BYTES, &tm_x, even_tile(s), bar_full + 8 * s);
        };
#pragma unroll
        for (int c = 0; c < 6; c++) {
            if (c == W_AHEAD) load_x(0);
            mbar_expect_tx(bar_w + 8 * c, CHUNK_BYTES);
            tma_load_w(smem + SMEM_W + c * CHUNK_BYTES, &tm_w, c * 64, rank * 3, bar_w + 8 * c);
        }
        for (int s = 1; s < NLOCAL; s++) load_x(s);
    }
    if (tid == 416) {
        for (int s = NLOCAL; s < STAGES; s++) mbar_init(bar_full + 8 * s, 1);
        for (int s = 0; s < STAGES; s++) mbar_init(bar_empty + 8 * s, 24);
        for (int s = 0; s < NBUF; s++) {
            mbar_init(bar_ofull + 8 * s, 12);
            mbar_init(bar_oempty + 8 * s, 1);
        }
        mbar_init(bar_wfree, 24);
        mbar_init(bar_wloc, 12);
        mbar_init(bar_spare, 1);
        mbar_init(bar_spare + 8, 1);
        sts(progress, 0);
        sts(total_slot, 0);
        sts(dry_slot, 0);
        sts(zero_slot, 0);
        asm volatile("fence.mbarrier_init.release.cluster;" ::: "memory");
        fence_async_smem();
        asm volatile("prefetch.tensormap [%0];" ::"l"(&tm_o) : "memory");
    }
    __syncwarp();
    asm volatile("barrier.cluster.arrive.relaxed.aligned;" ::: "memory");

    if (wg == 3) {
        if ((tid >> 5) == 14) {
            uint32_t due = EARLY_T;
#pragma unroll 1
            for (int j = 1; j < EARLY_N; j++, due += EARLY_DT) {
                while (now_ns() - t_entry < due) {}
                prefetch_half_tile(j);
            }
        }
        __syncwarp();
        asm volatile("barrier.cluster.wait.aligned;" ::: "memory");
        if (tid == 384 && rank == 0) {
            const uint32_t peer = mapa(smem, 1) - smem;
            const int shallow = max(ntiles - SHALLOW * nclusters, NSTATIC * UNIT * nclusters);
            int s = NLOCAL, n = 0;
            uint32_t ph = 1;
            int unit = cluster_id;
            for (int u = 0; unit < num_units; u++) {
                const bool late = unit * UNIT >= ntiles - 6 * nclusters;
                const unsigned long long t_fetch = late ? now_ns64() : 0;
                int next = unit - (NSTATIC - 1) * nclusters;
                if (u >= NSTATIC - 1) next = (int)atomicInc(&g_sched, (unsigned)(num_units - (NSTATIC - 1) * nclusters - 1));
#pragma unroll 1
                for (int h = 0; h < UNIT; h++, n++) {
                    if (n < NLOCAL) continue;
                    const int tile = unit * UNIT + h;
                    if (n == FREE_STAGES) mbar_wait(bar_wfree, 0);
                    mbar_wait(bar_empty + 8 * s, ph);
                    if (tile >= shallow) mbar_wait(bar_empty + 8 * ((s + 1) & 3), s == 3 ? ph ^ 1 : ph);
                    const uint32_t bar = bar_full + 8 * s;
                    tma_load_x_multicast(smem + s * STAGE_BYTES, &tm_x, tile, bar);
                    post_tile(bar, tile_slot + 4 * (n & 31), STAGE_BYTES + 4, tile);
                    post_tile(bar + peer, tile_slot + 4 * (n & 31) + peer, STAGE_BYTES + 4, tile);
                    sts_cluster(progress + peer, unit * UNIT + h * nclusters);
                    if (++s == STAGES) { s = 0; ph ^= 1; }
                    if (late && h == 0) {
                        asm volatile("" : "+r"(next)::"memory");
                        const int succ = next + NSTATIC * nclusters;
                        if (succ >= num_units) {
                            sts(total_slot, n + UNIT);
                            sts_cluster(total_slot + peer, n + UNIT);
                        }
                        if (succ == num_units - 1)
                            asm volatile("st.relaxed.gpu.global.b64 [%0], %1;" ::"l"(&g_dry), "l"(t_fetch) : "memory");
                    }
                }
                asm volatile("" : "+r"(next)::"memory");
                unit = next + NSTATIC * nclusters;
            }
            sts(total_slot, n);
            sts_cluster(total_slot + peer, n);
            sts_cluster(progress + peer, 0x7fffffff);
            mbar_wait(bar_empty + 8 * s, ph);
            post_tile(bar_full + 8 * s, tile_slot + 4 * (n & 31), 4, -1);
            post_tile(bar_full + 8 * s + peer, tile_slot + 4 * (n & 31) + peer, 4, -1);
#pragma unroll 1
            for (int e = 1; e < STAGES; e++) {
                if (++s == STAGES) { s = 0; ph ^= 1; }
                mbar_wait(bar_empty + 8 * s, ph);
            }
        } else if (tid == 448 && rank == 1) {
            auto wait_loader = [&](int tile, uint32_t unless) {
                while (lds(progress) < tile && lds(unless) == 0 && now_ns() - t_entry < 1000000000u) __nanosleep(64);
            };
            const int slope = (RA_LEAD - RA_MIN) * 256 / (RA_END - RA_FADE);
            int lead = RA_LEAD * 256;
            uint32_t due = RA_T0;
#pragma unroll 1
            for (int j = EARLY_N; j / UNIT * nclusters < num_units; j++, due += RA_DT) {
                const int t = even_tile(j);
                if (j >= RA_FADE && j < RA_END) lead -= slope;
                wait_loader(cluster_id * UNIT + j * nclusters - (lead * nclusters >> 10), dry_slot);
                while (now_ns() - t_entry < due) {}
                if (t < ntiles) l2_prefetch_tile(&tm_p, t);
            }
            wait_loader(0x7fffffff, zero_slot);
        } else if (tid == 384 || tid == 448) {
            const unsigned long long t_start = now_ns64();
            for (uint32_t it = 0; it < (1u << 22); it++) {
                unsigned long long v;
                asm volatile("ld.relaxed.gpu.global.b64 %0, [%1];" : "=l"(v) : "l"(&g_dry) : "memory");
                if (v > t_start) { sts(dry_slot, (uint32_t)v | 1); break; }
                if (lds(dry_slot)) break;
                __nanosleep(200);
            }
            if (atomicInc(&g_seen, gridDim.x - 1) == gridDim.x - 1)
                asm volatile("st.relaxed.gpu.global.b64 [%0], %1;" ::"l"(&g_dry), "l"(0ull) : "memory");
        } else if ((tid & 63) == 32) {
            uint32_t base = smem;
            asm volatile("" : "+r"(base));
            const uint32_t ofull = base + (bar_ofull - smem), otile = base + (tile_slot - smem);
            const uint32_t total_at = base + (total_slot - smem);
            int k = (tid >> 6) & 1;
            auto wait_filled = [&](int j) -> bool {
                const uint32_t lap = (uint32_t)j / NBUF, bar = ofull + 8 * (j - lap * NBUF);
                for (uint32_t it = 0; it < (1u << 22); it++) {
                    if (mbar_try(bar, lap & 1)) return true;
                    const int total = lds(total_at);
                    if (total != 0 && j >= total) break;
                }
                return false;
            };
            auto test_filled = [&](int j) -> bool {
                const uint32_t lap = (uint32_t)j / NBUF;
                return mbar_test(ofull + 8 * (j - lap * NBUF), lap & 1);
            };
            const int skew = cluster_id & 1;
            auto trigger = [&]() -> int { return k + min(max(0, RAMP_0 + (k + skew) * RAMP_Q) >> 4, NBUF - 1); };
            auto store = [&]() -> int {
                const int tile = lds(otile + 4 * (k & 31));
                const uint32_t slot = (uint32_t)k % NBUF;
                tma_store_out(&tm_o, base + SMEM_OUT + slot * OUT_BYTES, rank * 3, tile);
                asm volatile("cp.async.bulk.wait_group.read 0;" ::: "memory");
                mbar_arrive(ofull + 8 * (NBUF + slot));
                k += 2;
                return tile;
            };
            const int near_end = ntiles - (KREG + 2 * NBUF) * nclusters;
            while (wait_filled(trigger()))
                if (store() >= near_end) break;
            uint32_t t_dry = 0, due = 0;
            for (uint32_t it = 0; it < (1u << 22); it++) {
                int total = lds(total_at);
                const int m = trigger();
                if ((total == 0 || m < total) && test_filled(m)) { store(); continue; }
                t_dry = lds(base + (dry_slot - smem));
                if (t_dry) {
                    if (total == 0) total = m + KREG + STAGES + DRAIN_PRE;
                    due = t_dry + max(DRAIN_T0, DRAIN_END - (total - k) * DRAIN_DT);
                    if ((int)(now_ns() - due) >= 0) break;
                } else if (total != 0 && total <= m + 1 && test_filled(total - 1)) {
                    break;
                }
            }
            if (!t_dry) {
                due = now_ns();
                t_dry = (due - DRAIN_END) | 1;
                sts(base + (dry_slot - smem), t_dry);
            }
            uint32_t prev = base + (bar_spare - smem) + 8 * (k & 1);
            while (true) {
                const int total = lds(total_at);
                if (total != 0) {
                    if (k >= total) break;
                    due = t_dry + DRAIN_END - (total - k) * DRAIN_DT;
                }
                if (!wait_filled(k)) break;
                const int tile = lds(otile + 4 * (k & 31));
                const uint32_t slot = (uint32_t)k % NBUF;
                while ((int)(now_ns() - due) < 0) {}
                tma_store_out(&tm_o, base + SMEM_OUT + slot * OUT_BYTES, rank * 3, tile);
                asm volatile("cp.async.bulk.wait_group.read 1;" ::: "memory");
                mbar_arrive(prev);
                prev = ofull + 8 * (NBUF + slot);
                k += 2;
                due += 2 * DRAIN_DT;
            }
            asm volatile("cp.async.bulk.wait_group.read 0;" ::: "memory");
        }
    } else {
        asm volatile("setmaxnreg.inc.sync.aligned.u32 160;");
        const int lane = tid & 31;
        const int warp = (tid >> 5) & 3;
        if (wg == 2) asm volatile("bar.arrive 8, 256;" ::: "memory");

        uint32_t bias2;
        {
            const unsigned short* bp =
                reinterpret_cast<const unsigned short*>(bias) + rank * 192 + wg * 64 + warp * 16 + (lane >> 2);
            const uint32_t b0 = bp[0], b1 = bp[8];
            bias2 = b0 | (b1 << 16);
        }
        const uint32_t swz = (uint32_t)(((warp * 2 + ((lane >> 3) & 1)) ^ (lane & 7)) << 4);
        const uint32_t lead = mapa(smem, 0) - smem;

        const uint64_t desc0 = (uint64_t)((smem & 0x3FFFF) >> 4) | (1ull << 16) | ((6144ull >> 4) << 32) | (1ull << 62);
        float d[16];
        uint32_t a[24][4];
        asm volatile("barrier.cluster.wait.aligned;" ::: "memory");
        {
            const uint32_t base = smem + SMEM_W + wg * 8192 + ((lane >> 4) * 8 + (lane & 7)) * 128 + swz;
#pragma unroll
            for (int c = 0; c < 6; c++) {
                mbar_wait(bar_w + 8 * c, 0);
#pragma unroll
                for (int ks = 4 * c; ks < 4 * c + 4; ks++)
                    asm volatile("ldmatrix.sync.aligned.m8n8.x4.trans.shared.b16 {%0,%1,%2,%3}, [%4];"
                                 : "=r"(a[ks][0]), "=r"(a[ks][1]), "=r"(a[ks][2]), "=r"(a[ks][3])
                                 : "r"(base + c * CHUNK_BYTES + (ks & 3) * 2048) : "memory");
                if (c < W_AHEAD - 1) continue;
                if (c == W_AHEAD - 1) mbar_wait(bar_full, 0);
                asm volatile("wgmma.fence.sync.aligned;" ::: "memory");
#pragma unroll
                for (int ks = c == W_AHEAD - 1 ? 0 : 4 * c; ks < 4 * c + 4; ks++)
                    wgmma_rs(d, a[ks], desc0 + (uint64_t)(((ks >> 2) * 1024 + (ks & 3) * 32) >> 4), ks != 0);
            }
            asm volatile("wgmma.commit_group.sync.aligned;" ::: "memory");
        }
        fence_async_smem();
        __syncwarp();
        if (lane == 0) {
            mbar_arrive_cluster(bar_wfree + lead);
            mbar_arrive(bar_wloc);
        }
        asm volatile("wgmma.wait_group.sync.aligned 0;" ::: "memory");
#pragma unroll
        for (int j = 0; j < 16; j++) asm volatile("" : "+f"(d[j])::"memory");
        if (lane == 0) mbar_arrive_cluster(bar_empty + lead);

        uint32_t st_base = smem + SMEM_OUT + wg * 1024 + (lane >> 4) * 3072 + (lane & 7) * 128 + swz;
        const int wgu = __shfl_sync(0xffffffffu, wg, 0);
        asm volatile("" : "+r"(st_base), "+r"(bias2));

        int s = 1, ob = 0, i = 1;
        uint32_t ph = 0, oph = 1;
        uint32_t q[KREG][8];
        auto compute = [&]() -> bool {
            mbar_wait(bar_full + 8 * s, ph);
            if (lds(tile_slot + 4 * (i & 31)) < 0) return false;
            const uint64_t desc = desc0 + (uint64_t)(s * (STAGE_BYTES >> 4));
            asm volatile("bar.sync %0, 256;" ::"r"(8 + wgu) : "memory");
            asm volatile("wgmma.fence.sync.aligned;" ::: "memory");
#pragma unroll
            for (int ks = 0; ks < 24; ks++) {
                wgmma_rs(d, a[ks], desc + (uint64_t)(((ks >> 2) * 1024 + (ks & 3) * 32) >> 4), ks != 0);
                if (ks == HANDOVER - 1) asm volatile("bar.arrive %0, 256;" ::"r"(wgu == 2 ? 8 : 9 + wgu) : "memory");
            }
            asm volatile("wgmma.commit_group.sync.aligned;" ::: "memory");
            asm volatile("wgmma.wait_group.sync.aligned 0;" ::: "memory");
#pragma unroll
            for (int j = 0; j < 16; j++) asm volatile("" : "+f"(d[j])::"memory");
            if (lane == 0) mbar_arrive_cluster(bar_empty + 8 * s + lead);
            if (++s == STAGES) { s = 0; ph ^= 1; }
            return true;
        };
        auto pack = [&](uint32_t (&p)[8]) {
#pragma unroll
            for (int j = 0; j < 8; j += 2) {
                p[j]     = cvt_add_bias<false>(d[2 * j], d[2 * j + 1], bias2);
                p[j + 1] = cvt_add_bias<true>(d[2 * j + 2], d[2 * j + 3], bias2);
            }
        };
        auto put = [&](uint32_t st, const uint32_t (&p)[8]) {
#pragma unroll
            for (int j = 0; j < 2; j++)
                asm volatile("stmatrix.sync.aligned.m8n8.x4.trans.shared.b16 [%0], {%1,%2,%3,%4};"
                             ::"r"(st + j * 6144), "r"(p[4 * j]), "r"(p[4 * j + 1]), "r"(p[4 * j + 2]), "r"(p[4 * j + 3])
                             : "memory");
        };
        auto acquire = [&]() -> uint32_t {
            mbar_wait(bar_oempty + 8 * ob, oph);
            return st_base + ob * OUT_BYTES;
        };
        auto publish = [&]() {
            fence_async_smem();
            __syncwarp();
            if (lane == 0) mbar_arrive(bar_ofull + 8 * ob);
            if (++ob == NBUF) { ob = 0; oph ^= 1; }
        };

        const int kstart = KSTART - cluster_id % KRAMP;
        int held = 0, h = 0;
        bool more = true;
        pack(q[0]);
        mbar_wait(bar_wloc, 0);
        put(acquire(), q[0]);
        publish();
#pragma unroll 1
        for (; i < kstart; i++) {
            more = compute();
            if (!more) break;
            pack(q[0]);
            put(acquire(), q[0]);
            publish();
        }
        if (more) {
            int kstep = kstart;
#pragma unroll 1
            for (; compute(); i++) {
                if (h == 0 && i >= kstep) {
#pragma unroll
                    for (int k = 0; k < KREG; k++)
                        if (held == k) pack(q[k]);
                    kstep = ++held == KREG ? 0x7fffffff : kstep + KRAMP;
                    continue;
                }
                const uint32_t st = acquire();
#pragma unroll
                for (int k = 0; k < KREG; k++)
                    if (h == k) { put(st, q[k]); pack(q[k]); }
                publish();
                if (++h == held) h = 0;
            }
#pragma unroll 1
            for (int left = held; left > 0; left--) {
                const uint32_t st = acquire();
#pragma unroll
                for (int k = 0; k < KREG; k++)
                    if (h == k) put(st, q[k]);
                publish();
                if (++h == held) h = 0;
            }
        }
        if (wg == 0) asm volatile("bar.sync 8, 256;" ::: "memory");
    }
}

typedef CUresult (*EncodeTiledFn)(CUtensorMap*, CUtensorMapDataType, cuuint32_t, void*, const cuuint64_t*,
                                  const cuuint64_t*, const cuuint32_t*, const cuuint32_t*, CUtensorMapInterleave,
                                  CUtensorMapSwizzle, CUtensorMapL2promotion, CUtensorMapFloatOOBfill);

void encode_map(EncodeTiledFn fn, CUtensorMap* tm, const void* ptr, int rank, const cuuint64_t* dims,
                const cuuint64_t* strides, const cuuint32_t* box) {
    const cuuint32_t estr[4] = {1, 1, 1, 1};
    fn(tm, CU_TENSOR_MAP_DATA_TYPE_BFLOAT16, rank, const_cast<void*>(ptr), dims, strides, box, estr,
       CU_TENSOR_MAP_INTERLEAVE_NONE, CU_TENSOR_MAP_SWIZZLE_128B, CU_TENSOR_MAP_L2_PROMOTION_L2_128B,
       CU_TENSOR_MAP_FLOAT_OOB_FILL_NONE);
}

}

extern "C" void kernel_launch(void* const* d_in, const int* in_sizes, int n_in, void* d_out, int out_size) {
    const __nv_bfloat16* x = (const __nv_bfloat16*)d_in[0];
    const __nv_bfloat16* w = (const __nv_bfloat16*)d_in[1];
    const __nv_bfloat16* b = (const __nv_bfloat16*)d_in[2];
    const int pixels = in_sizes[0] / C;

    static EncodeTiledFn encode = nullptr;
    static int max_clusters = 0;
    if (!encode) {
        void* fn = nullptr;
        cudaDriverEntryPointQueryResult qr;
        cudaGetDriverEntryPoint("cuTensorMapEncodeTiled", &fn, cudaEnableDefault, &qr);
        encode = (EncodeTiledFn)fn;
        cudaFuncSetAttribute(conv1x1_kernel, cudaFuncAttributeMaxDynamicSharedMemorySize, SMEM_TOTAL);
        cudaLaunchConfig_t cfg = {};
        cfg.gridDim = dim3(2, 1, 1);
        cfg.blockDim = dim3(NTHREADS, 1, 1);
        cfg.dynamicSmemBytes = SMEM_TOTAL;
        cudaLaunchAttribute at[1];
        at[0].id = cudaLaunchAttributeClusterDimension;
        at[0].val.clusterDim.x = 2; at[0].val.clusterDim.y = 1; at[0].val.clusterDim.z = 1;
        cfg.attrs = at; cfg.numAttrs = 1;
        if (cudaOccupancyMaxActiveClusters(&max_clusters, conv1x1_kernel, &cfg) != cudaSuccess || max_clusters <= 0) {
            (void)cudaGetLastError();
            int dev = 0, sms = 0;
            cudaGetDevice(&dev);
            cudaDeviceGetAttribute(&sms, cudaDevAttrMultiProcessorCount, dev);
            max_clusters = sms / 2;
        }
    }
    CUtensorMap tm_x, tm_w, tm_o, tm_p;
    {
        const cuuint64_t dims[4]    = {64, 8, 6, (cuuint64_t)(pixels / 8)};
        const cuuint64_t strides[3] = {C * 2, 128, C * 2 * 8};
        const cuuint32_t box_x[4]   = {64, 8, 6, TP / 8};
        const cuuint32_t box_o[4]   = {64, 8, 3, TP / 8};
        encode_map(encode, &tm_x, x, 4, dims, strides, box_x);
        encode_map(encode, &tm_o, d_out, 4, dims, strides, box_o);
        const cuuint64_t pdims[2]    = {64, (cuuint64_t)pixels * 6};
        const cuuint64_t pstrides[1] = {128};
        const cuuint32_t pbox[2]     = {64, STAGE_BYTES / 128};
        encode_map(encode, &tm_p, x, 2, pdims, pstrides, pbox);
        const cuuint64_t wdims[3]    = {64, C, 6};
        const cuuint64_t wstrides[2] = {C * 2, 128};
        const cuuint32_t wbox[3]     = {64, 64, 3};
        encode_map(encode, &tm_w, w, 3, wdims, wstrides, wbox);
    }
    const int num_units = pixels / (TP * UNIT);
    const int nclusters = max_clusters * NSTATIC <= num_units ? max_clusters : num_units / NSTATIC;
    conv1x1_kernel<<<2 * nclusters, NTHREADS, SMEM_TOTAL, cudaStreamPerThread>>>(x, w, b, num_units, tm_x, tm_w, tm_o, tm_p);
}
```

```cpp
#include <cuda_runtime.h>
#include <cuda_bf16.h>
#include <cuda.h>
#include <stdint.h>

#define TUNE(name, value) constexpr int name = value
TUNE(RAMP_Q, 11);
TUNE(RAMP_0, -15);
TUNE(KSTART, 27);
TUNE(KRAMP, 4);
TUNE(EARLY_N, 4);
TUNE(EARLY_T, 350);
TUNE(EARLY_DT, 315);
TUNE(RA_T0, 1515);
TUNE(RA_DT, 468);
TUNE(RA_LEAD, 39);
TUNE(RA_FADE, 9);
TUNE(RA_END, 66);
TUNE(RA_MIN, 8);
TUNE(SHALLOW, 13);
TUNE(DRAIN_T0, 600);
TUNE(DRAIN_END, 11230);
TUNE(DRAIN_DT, 470);
TUNE(DRAIN_PRE, 1);

namespace {

constexpr int C           = 384;
constexpr int TP          = 32;
constexpr int UNIT        = 2;
constexpr int NSTATIC     = 4;
constexpr int KREG        = 5;
constexpr int HANDOVER    = 18;
constexpr int STAGES      = 4;
constexpr int NBUF        = 10;
constexpr int NLOCAL      = 2;
constexpr int STAGE_BYTES = TP * C * 2;
constexpr int OUT_BYTES   = TP * 192 * 2;
constexpr int CHUNK_BYTES = 64 * 192 * 2;
constexpr int W_AHEAD     = 3;
constexpr int SMEM_OUT    = STAGES * STAGE_BYTES;
constexpr int SMEM_BAR    = SMEM_OUT + NBUF * OUT_BYTES;
constexpr int SMEM_TOTAL  = SMEM_BAR + 512 + 1024;
constexpr int NTHREADS    = 512;
constexpr int SMEM_W      = SMEM_BAR - 6 * CHUNK_BYTES;
constexpr int FREE_STAGES = SMEM_W / STAGE_BYTES;
static_assert(SMEM_W % 1024 == 0 && NLOCAL == 2 && NLOCAL <= FREE_STAGES && FREE_STAGES < NSTATIC * UNIT, "layout");
static_assert(SMEM_W + W_AHEAD * CHUNK_BYTES >= SMEM_OUT + 2 * OUT_BYTES, "early release of the W staging area");
static_assert(STAGES == 4 && NSTATIC * UNIT >= STAGES, "the shallow mode of the loader assumes four stages");
static_assert(SMEM_TOTAL <= 232448, "too much shared memory");

__device__ unsigned int g_sched;
__device__ unsigned long long g_dry;
__device__ unsigned int g_seen;

__device__ __forceinline__ uint32_t smem_u32(const void* p) { return (uint32_t)__cvta_generic_to_shared(p); }
__device__ __forceinline__ uint32_t now_ns() {
    uint32_t t;
    asm volatile("mov.u32 %0, %%globaltimer_lo;" : "=r"(t));
    return t;
}
__device__ __forceinline__ unsigned long long now_ns64() {
    unsigned long long t;
    asm volatile("mov.u64 %0, %%globaltimer;" : "=l"(t));
    return t;
}
__device__ __forceinline__ int lds(uint32_t addr) {
    int v;
    asm volatile("ld.volatile.shared.b32 %0, [%1];" : "=r"(v) : "r"(addr) : "memory");
    return v;
}
__device__ __forceinline__ void sts(uint32_t addr, int v) {
    asm volatile("st.volatile.shared.b32 [%0], %1;" ::"r"(addr), "r"(v) : "memory");
}
__device__ __forceinline__ void sts_cluster(uint32_t cluster_addr, int v) {
    asm volatile("st.volatile.shared::cluster.b32 [%0], %1;" ::"r"(cluster_addr), "r"(v) : "memory");
}
__device__ __forceinline__ void mbar_init(uint32_t bar, uint32_t count) {
    asm volatile("mbarrier.init.shared::cta.b64 [%0], %1;" ::"r"(bar), "r"(count) : "memory");
}
__device__ __forceinline__ void mbar_expect_tx(uint32_t bar, uint32_t bytes) {
    asm volatile("mbarrier.arrive.expect_tx.shared::cta.b64 _, [%0], %1;" ::"r"(bar), "r"(bytes) : "memory");
}
__device__ __forceinline__ void mbar_arrive(uint32_t bar) {
    asm volatile("mbarrier.arrive.shared::cta.b64 _, [%0];" ::"r"(bar) : "memory");
}
__device__ __forceinline__ void mbar_arrive_cluster(uint32_t cluster_addr) {
    asm volatile("mbarrier.arrive.shared::cluster.b64 _, [%0];" ::"r"(cluster_addr) : "memory");
}
__device__ __forceinline__ bool mbar_try(uint32_t bar, uint32_t parity) {
    uint32_t ok;
    asm volatile("{\n.reg .pred p;\nmbarrier.try_wait.parity.shared::cta.b64 p, [%1], %2;\nselp.u32 %0, 1, 0, p;\n}"
                 : "=r"(ok) : "r"(bar), "r"(parity) : "memory");
    return ok;
}
__device__ __forceinline__ bool mbar_test(uint32_t bar, uint32_t parity) {
    uint32_t ok;
    asm volatile("{\n.reg .pred p;\nmbarrier.test_wait.parity.shared::cta.b64 p, [%1], %2;\nselp.u32 %0, 1, 0, p;\n}"
                 : "=r"(ok) : "r"(bar), "r"(parity) : "memory");
    return ok;
}
__device__ __forceinline__ void mbar_wait(uint32_t bar, uint32_t parity) {
    asm volatile("{\n.reg .pred p, q;\n.reg .u32 n;\n"
                 "mbarrier.try_wait.parity.shared::cta.b64 p, [%0], %1;\n@p bra DONE;\nmov.u32 n, 0;\n"
                 "AGAIN:\nmbarrier.try_wait.parity.shared::cta.b64 p, [%0], %1;\nadd.u32 n, n, 1;\n"
                 "setp.lt.and.u32 q, n, 0x400000, !p;\n@q bra AGAIN;\nDONE:\n}"
                 ::"r"(bar), "r"(parity) : "memory");
}
__device__ __forceinline__ uint32_t mapa(uint32_t addr, uint32_t rank) {
    uint32_t r;
    asm("mapa.shared::cluster.u32 %0, %1, %2;" : "=r"(r) : "r"(addr), "r"(rank));
    return r;
}
__device__ __forceinline__ void fence_async_smem() { asm volatile("fence.proxy.async.shared::cta;" ::: "memory"); }
__device__ __forceinline__ void post_tile(uint32_t bar, uint32_t slot, uint32_t bytes, int value) {
    asm volatile("mbarrier.arrive.expect_tx.shared::cluster.b64 _, [%0], %1;" ::"r"(bar), "r"(bytes) : "memory");
    asm volatile("st.async.weak.shared::cluster.mbarrier::complete_tx::bytes.b32 [%0], %1, [%2];"
                 ::"r"(slot), "r"(value), "r"(bar) : "memory");
}
__device__ __forceinline__ void tma_load_w(uint32_t dst, const CUtensorMap* tm, int k, int slab, uint32_t bar) {
    asm volatile("cp.async.bulk.tensor.3d.shared::cluster.global.mbarrier::complete_tx::bytes [%0], [%1, {%3, %4, %5}], [%2];"
                 ::"r"(dst), "l"(tm), "r"(bar), "r"(0), "r"(k), "r"(slab) : "memory");
}
__device__ __forceinline__ void tma_load_x(uint32_t dst, const CUtensorMap* tm, int tile, uint32_t bar) {
    asm volatile("cp.async.bulk.tensor.4d.shared::cluster.global.mbarrier::complete_tx::bytes"
                 " [%0], [%1, {%4, %4, %4, %3}], [%2];"
                 ::"r"(dst), "l"(tm), "r"(bar), "r"(tile * (TP / 8)), "r"(0) : "memory");
}
__device__ __forceinline__ void tma_load_x_multicast(uint32_t dst, const CUtensorMap* tm, int tile, uint32_t bar) {
    asm volatile("cp.async.bulk.tensor.4d.shared::cluster.global.mbarrier::complete_tx::bytes.multicast::cluster"
                 " [%0], [%1, {%4, %4, %4, %3}], [%2], %5;"
                 ::"r"(dst), "l"(tm), "r"(bar), "r"(tile * (TP / 8)), "r"(0), "h"((uint16_t)3) : "memory");
}
__device__ __forceinline__ void tma_store_out(const CUtensorMap* tm, uint32_t src, int slab, int tile) {
    asm volatile("cp.async.bulk.tensor.4d.global.shared::cta.bulk_group [%0, {%4, %4, %2, %3}], [%1];"
                 ::"l"(tm), "r"(src), "r"(slab), "r"(tile * (TP / 8)), "r"(0) : "memory");
    asm volatile("cp.async.bulk.commit_group;" ::: "memory");
}
__device__ __forceinline__ void l2_prefetch_tile(const CUtensorMap* tm, int tile) {
    asm volatile("cp.async.bulk.prefetch.tensor.2d.L2.global.tile [%0, {%1, %2}];"
                 ::"l"(tm), "r"(0), "r"(tile * (STAGE_BYTES / 128)) : "memory");
}

__device__ __forceinline__ void wgmma_rs(float (&d)[16], const uint32_t (&a)[4], uint64_t desc, int scale_d) {
    asm volatile(
        "{\n.reg .pred p;\nsetp.ne.b32 p, %21, 0;\n"
        "wgmma.mma_async.sync.aligned.m64n32k16.f32.bf16.bf16 "
        "{%0,%1,%2,%3,%4,%5,%6,%7,%8,%9,%10,%11,%12,%13,%14,%15},"
        "{%16,%17,%18,%19}, %20, p, 1, 1, 0;\n}"
        : "+f"(d[0]), "+f"(d[1]), "+f"(d[2]), "+f"(d[3]), "+f"(d[4]), "+f"(d[5]), "+f"(d[6]), "+f"(d[7]),
          "+f"(d[8]), "+f"(d[9]), "+f"(d[10]), "+f"(d[11]), "+f"(d[12]), "+f"(d[13]), "+f"(d[14]), "+f"(d[15])
        : "r"(a[0]), "r"(a[1]), "r"(a[2]), "r"(a[3]), "l"(desc), "r"(scale_d));
}
template <bool HI>
__device__ __forceinline__ uint32_t cvt_add_bias(float lo, float hi, uint32_t bias2) {
    uint32_t r;
    if (HI) asm("{\n.reg .b32 t, b;\n.reg .b16 l, h;\ncvt.rn.bf16x2.f32 t, %2, %1;\nmov.b32 {l, h}, %3;\nmov.b32 b, {h, h};\n"
                "add.rn.bf16x2 %0, t, b;\n}" : "=r"(r) : "f"(lo), "f"(hi), "r"(bias2));
    else asm("{\n.reg .b32 t, b;\n.reg .b16 l, h;\ncvt.rn.bf16x2.f32 t, %2, %1;\nmov.b32 {l, h}, %3;\nmov.b32 b, {l, l};\n"
             "add.rn.bf16x2 %0, t, b;\n}" : "=r"(r) : "f"(lo), "f"(hi), "r"(bias2));
    return r;
}

__global__ void __cluster_dims__(2, 1, 1) __launch_bounds__(NTHREADS, 1)
conv1x1_kernel(const __nv_bfloat16* __restrict__ x, const __nv_bfloat16* __restrict__ w,
               const __nv_bfloat16* __restrict__ bias, int num_units,
               const __grid_constant__ CUtensorMap tm_x, const __grid_constant__ CUtensorMap tm_w,
               const __grid_constant__ CUtensorMap tm_o, const __grid_constant__ CUtensorMap tm_p) {
    extern __shared__ uint8_t smem_raw[];
    const uint32_t smem = (smem_u32(smem_raw) + 1023u) & ~1023u;
    const uint32_t bar_full   = smem + SMEM_BAR;
    const uint32_t bar_empty  = bar_full + 8 * STAGES;
    const uint32_t bar_ofull  = bar_empty + 8 * STAGES;
    const uint32_t bar_oempty = bar_ofull + 8 * NBUF;
    const uint32_t bar_w      = bar_oempty + 8 * NBUF;
    const uint32_t bar_wfree  = bar_w + 48;
    const uint32_t bar_wloc   = bar_wfree + 8;
    const uint32_t bar_spare  = bar_wloc + 8;
    const uint32_t progress   = bar_spare + 16;
    const uint32_t total_slot = progress + 4;
    const uint32_t dry_slot   = progress + 8;
    const uint32_t zero_slot  = progress + 12;
    const uint32_t tile_slot  = progress + 16;

    const int tid = threadIdx.x;
    const int wg  = tid >> 7;
    uint32_t rank;
    asm("mov.u32 %0, %%cluster_ctarank;" : "=r"(rank));
    const int cluster_id = blockIdx.x >> 1;
    const int nclusters  = gridDim.x >> 1;
    const int ntiles     = num_units * UNIT;
    auto even_tile = [&](int j) { return (cluster_id + j / UNIT * nclusters) * UNIT + j % UNIT; };

    asm volatile("setmaxnreg.dec.sync.aligned.u32 32;");

    auto prefetch_lines = [&](const void* base, int bytes) {
        const char* p = static_cast<const char*>(base) + (tid & 31) * 128;
#pragma unroll
        for (int o = 0; o < bytes; o += 4096)
            if (o + 4096 <= bytes || (tid & 31) * 128 < bytes - o)
                asm volatile("prefetch.global.L2 [%0];" ::"l"(p + o) : "memory");
    };
    auto prefetch_half_tile = [&](int j) {
        prefetch_lines(x + (size_t)(even_tile(j) * TP + rank * (TP / 2)) * C, STAGE_BYTES / 2);
    };
    uint32_t t_entry = 0;
    if ((tid >> 5) == 14) {
        prefetch_lines(w + (blockIdx.x & 63) * (C * C / 64), C * C * 2 / 64);
        t_entry = now_ns();
        prefetch_half_tile(0);
        if (tid == 448) asm volatile("prefetch.tensormap [%0];" ::"l"(&tm_p) : "memory");
    }
    if (tid == 384) {
        asm volatile("prefetch.tensormap [%0];" ::"l"(&tm_w) : "memory");
        asm volatile("prefetch.tensormap [%0];" ::"l"(&tm_x) : "memory");
        for (int c = 0; c < 6; c++) mbar_init(bar_w + 8 * c, 1);
        for (int s = 0; s < NLOCAL; s++) mbar_init(bar_full + 8 * s, 1);
        asm volatile("fence.mbarrier_init.release.cluster;" ::: "memory");
        fence_async_smem();
        auto load_x = [&](int s) {
            sts(tile_slot + 4 * s, even_tile(s));
            mbar_expect_tx(bar_full + 8 * s, STAGE_BYTES);
            tma_load_x(smem + s * STAGE_BYTES, &tm_x, even_tile(s), bar_full + 8 * s);
        };
#pragma unroll
        for (int c = 0; c < 6; c++) {
            if (c == W_AHEAD) load_x(0);
            if (c == 5) load_x(1);
            mbar_expect_tx(bar_w + 8 * c, CHUNK_BYTES);
            tma_load_w(smem + SMEM_W + c * CHUNK_BYTES, &tm_w, c * 64, rank * 3, bar_w + 8 * c);
        }
    }
    if (tid == 416) {
        for (int s = NLOCAL; s < STAGES; s++) mbar_init(bar_full + 8 * s, 1);
        for (int s = 0; s < STAGES; s++) mbar_init(bar_empty + 8 * s, 24);
        for (int s = 0; s < NBUF; s++) {
            mbar_init(bar_ofull + 8 * s, 12);
            mbar_init(bar_oempty + 8 * s, 1);
        }
        mbar_init(bar_wfree, 24);
        mbar_init(bar_wloc, 12);
        mbar_init(bar_spare, 1);
        mbar_init(bar_spare + 8, 1);
        sts(progress, 0);
        sts(total_slot, 0);
        sts(dry_slot, 0);
        sts(zero_slot, 0);
        asm volatile("fence.mbarrier_init.release.cluster;" ::: "memory");
        fence_async_smem();
        asm volatile("prefetch.tensormap [%0];" ::"l"(&tm_o) : "memory");
    }
    __syncwarp();
    asm volatile("barrier.cluster.arrive.relaxed.aligned;" ::: "memory");

    if (wg == 3) {
        if ((tid >> 5) == 14) {
            uint32_t due = EARLY_T;
#pragma unroll 1
            for (int j = 1; j < EARLY_N; j++, due += EARLY_DT) {
                while (now_ns() - t_entry < due) {}
                prefetch_half_tile(j);
            }
        }
        __syncwarp();
        asm volatile("barrier.cluster.wait.aligned;" ::: "memory");
        if (tid == 384 && rank == 0) {
            const uint32_t peer = mapa(smem, 1) - smem;
            const int shallow = max(ntiles - SHALLOW * nclusters, NSTATIC * UNIT * nclusters);
            int s = NLOCAL, n = 0;
            uint32_t ph = 1;
            int unit = cluster_id;
            for (int u = 0; unit < num_units; u++) {
                const bool late = unit * UNIT >= ntiles - 6 * nclusters;
                const unsigned long long t_fetch = late ? now_ns64() : 0;
                int next = unit - (NSTATIC - 1) * nclusters;
                if (u >= NSTATIC - 1) next = (int)atomicInc(&g_sched, (unsigned)(num_units - (NSTATIC - 1) * nclusters - 1));
#pragma unroll 1
                for (int h = 0; h < UNIT; h++, n++) {
                    if (n < NLOCAL) continue;
                    const int tile = unit * UNIT + h;
                    if (n == FREE_STAGES) mbar_wait(bar_wfree, 0);
                    mbar_wait(bar_empty + 8 * s, ph);
                    if (tile >= shallow) mbar_wait(bar_empty + 8 * ((s + 1) & 3), s == 3 ? ph ^ 1 : ph);
                    const uint32_t bar = bar_full + 8 * s;
                    tma_load_x_multicast(smem + s * STAGE_BYTES, &tm_x, tile, bar);
                    post_tile(bar, tile_slot + 4 * (n & 31), STAGE_BYTES + 4, tile);
                    post_tile(bar + peer, tile_slot + 4 * (n & 31) + peer, STAGE_BYTES + 4, tile);
                    sts_cluster(progress + peer, unit * UNIT + h * nclusters);
                    if (++s == STAGES) { s = 0; ph ^= 1; }
                    if (late && h == 0) {
                        asm volatile("" : "+r"(next)::"memory");
                        const int succ = next + NSTATIC * nclusters;
                        if (succ >= num_units) {
                            sts(total_slot, n + UNIT);
                            sts_cluster(total_slot + peer, n + UNIT);
                        }
                        if (succ == num_units - 1)
                            asm volatile("st.relaxed.gpu.global.b64 [%0], %1;" ::"l"(&g_dry), "l"(t_fetch) : "memory");
                    }
                }
                asm volatile("" : "+r"(next)::"memory");
                unit = next + NSTATIC * nclusters;
            }
            sts(total_slot, n);
            sts_cluster(total_slot + peer, n);
            sts_cluster(progress + peer, 0x7fffffff);
            mbar_wait(bar_empty + 8 * s, ph);
            post_tile(bar_full + 8 * s, tile_slot + 4 * (n & 31), 4, -1);
            post_tile(bar_full + 8 * s + peer, tile_slot + 4 * (n & 31) + peer, 4, -1);
#pragma unroll 1
            for (int e = 1; e < STAGES; e++) {
                if (++s == STAGES) { s = 0; ph ^= 1; }
                mbar_wait(bar_empty + 8 * s, ph);
            }
        } else if (tid == 448 && rank == 1) {
            auto wait_loader = [&](int tile, uint32_t unless) {
                while (lds(progress) < tile && lds(unless) == 0 && now_ns() - t_entry < 1000000000u) __nanosleep(64);
            };
            const int slope = (RA_LEAD - RA_MIN) * 256 / (RA_END - RA_FADE);
            int lead = RA_LEAD * 256;
            uint32_t due = RA_T0;
#pragma unroll 1
            for (int j = EARLY_N; j / UNIT * nclusters < num_units; j++, due += RA_DT) {
                const int t = even_tile(j);
                if (j >= RA_FADE && j < RA_END) lead -= slope;
                wait_loader(cluster_id * UNIT + j * nclusters - (lead * nclusters >> 10), dry_slot);
                while (now_ns() - t_entry < due) {}
                if (t < ntiles) l2_prefetch_tile(&tm_p, t);
            }
            wait_loader(0x7fffffff, zero_slot);
        } else if (tid == 384 || tid == 448) {
            const unsigned long long t_start = now_ns64();
            for (uint32_t it = 0; it < (1u << 22); it++) {
                unsigned long long v;
                asm volatile("ld.relaxed.gpu.global.b64 %0, [%1];" : "=l"(v) : "l"(&g_dry) : "memory");
                if (v > t_start) { sts(dry_slot, (uint32_t)v | 1); break; }
                if (lds(dry_slot)) break;
                __nanosleep(200);
            }
            if (atomicInc(&g_seen, gridDim.x - 1) == gridDim.x - 1)
                asm volatile("st.relaxed.gpu.global.b64 [%0], %1;" ::"l"(&g_dry), "l"(0ull) : "memory");
        } else if ((tid & 63) == 32) {
            uint32_t base = smem;
            asm volatile("" : "+r"(base));
            const uint32_t ofull = base + (bar_ofull - smem), otile = base + (tile_slot - smem);
            const uint32_t total_at = base + (total_slot - smem);
            int k = (tid >> 6) & 1;
            auto wait_filled = [&](int j) -> bool {
                const uint32_t lap = (uint32_t)j / NBUF, bar = ofull + 8 * (j - lap * NBUF);
                for (uint32_t it = 0; it < (1u << 22); it++) {
                    if (mbar_try(bar, lap & 1)) return true;
                    const int total = lds(total_at);
                    if (total != 0 && j >= total) break;
                }
                return false;
            };
            auto test_filled = [&](int j) -> bool {
                const uint32_t lap = (uint32_t)j / NBUF;
                return mbar_test(ofull + 8 * (j - lap * NBUF), lap & 1);
            };
            const int skew = cluster_id & 1;
            auto trigger = [&]() -> int { return k + min(max(0, RAMP_0 + (k + skew) * RAMP_Q) >> 4, NBUF - 1); };
            auto store = [&]() -> int {
                const int tile = lds(otile + 4 * (k & 31));
                const uint32_t slot = (uint32_t)k % NBUF;
                tma_store_out(&tm_o, base + SMEM_OUT + slot * OUT_BYTES, rank * 3, tile);
                asm volatile("cp.async.bulk.wait_group.read 0;" ::: "memory");
                mbar_arrive(ofull + 8 * (NBUF + slot));
                k += 2;
                return tile;
            };
            const int near_end = ntiles - (KREG + 2 * NBUF) * nclusters;
            while (wait_filled(trigger()))
                if (store() >= near_end) break;
            uint32_t t_dry = 0, due = 0;
            for (uint32_t it = 0; it < (1u << 22); it++) {
                int total = lds(total_at);
                const int m = trigger();
                if ((total == 0 || m < total) && test_filled(m)) { store(); continue; }
                t_dry = lds(base + (dry_slot - smem));
                if (t_dry) {
                    if (total == 0) total = m + KREG + STAGES + DRAIN_PRE;
                    due = t_dry + max(DRAIN_T0, DRAIN_END - (total - k) * DRAIN_DT);
                    if ((int)(now_ns() - due) >= 0) break;
                } else if (total != 0 && total <= m + 1 && test_filled(total - 1)) {
                    break;
                }
            }
            if (!t_dry) {
                due = now_ns();
                t_dry = (due - DRAIN_END) | 1;
                sts(base + (dry_slot - smem), t_dry);
            }
            uint32_t prev = base + (bar_spare - smem) + 8 * (k & 1);
            while (true) {
                const int total = lds(total_at);
                if (total != 0) {
                    if (k >= total) break;
                    due = t_dry + DRAIN_END - (total - k) * DRAIN_DT;
                }
                if (!wait_filled(k)) break;
                const int tile = lds(otile + 4 * (k & 31));
                const uint32_t slot = (uint32_t)k % NBUF;
                while ((int)(now_ns() - due) < 0) {}
                tma_store_out(&tm_o, base + SMEM_OUT + slot * OUT_BYTES, rank * 3, tile);
                asm volatile("cp.async.bulk.wait_group.read 1;" ::: "memory");
                mbar_arrive(prev);
                prev = ofull + 8 * (NBUF + slot);
                k += 2;
                due += 2 * DRAIN_DT;
            }
            asm volatile("cp.async.bulk.wait_group.read 0;" ::: "memory");
        }
    } else {
        asm volatile("setmaxnreg.inc.sync.aligned.u32 160;");
        const int lane = tid & 31;
        const int warp = (tid >> 5) & 3;
        if (wg == 2) asm volatile("bar.arrive 8, 256;" ::: "memory");

        uint32_t bias2;
        {
            const unsigned short* bp =
                reinterpret_cast<const unsigned short*>(bias) + rank * 192 + wg * 64 + warp * 16 + (lane >> 2);
            const uint32_t b0 = bp[0], b1 = bp[8];
            bias2 = b0 | (b1 << 16);
        }
        const uint32_t swz = (uint32_t)(((warp * 2 + ((lane >> 3) & 1)) ^ (lane & 7)) << 4);
        const uint32_t lead = mapa(smem, 0) - smem;

        const uint64_t desc0 = (uint64_t)((smem & 0x3FFFF) >> 4) | (1ull << 16) | ((6144ull >> 4) << 32) | (1ull << 62);
        float d[16];
        const int wgu = __shfl_sync(0xffffffffu, wg, 0);
        uint32_t a[24][4];
        asm volatile("barrier.cluster.wait.aligned;" ::: "memory");
        {
            const uint32_t base = smem + SMEM_W + wg * 8192 + ((lane >> 4) * 8 + (lane & 7)) * 128 + swz;
#pragma unroll
            for (int c = 0; c < 6; c++) {
                mbar_wait(bar_w + 8 * c, 0);
#pragma unroll
                for (int ks = 4 * c; ks < 4 * c + 4; ks++)
                    asm volatile("ldmatrix.sync.aligned.m8n8.x4.trans.shared.b16 {%0,%1,%2,%3}, [%4];"
                                 : "=r"(a[ks][0]), "=r"(a[ks][1]), "=r"(a[ks][2]), "=r"(a[ks][3])
                                 : "r"(base + c * CHUNK_BYTES + (ks & 3) * 2048) : "memory");
                if (c < W_AHEAD - 1) continue;
                if (c == W_AHEAD - 1) {
                    fence_async_smem();
                    __syncwarp();
                    if (lane == 0) {
                        mbar_arrive_cluster(bar_wfree + lead);
                        mbar_arrive(bar_wloc);
                    }
                    mbar_wait(bar_full, 0);
                    asm volatile("bar.sync %0, 256;" ::"r"(8 + wgu) : "memory");
                }
                asm volatile("wgmma.fence.sync.aligned;" ::: "memory");
#pragma unroll
                for (int ks = c == W_AHEAD - 1 ? 0 : 4 * c; ks < 4 * c + 4; ks++) {
                    wgmma_rs(d, a[ks], desc0 + (uint64_t)(((ks >> 2) * 1024 + (ks & 3) * 32) >> 4), ks != 0);
                    if (ks == 4 * W_AHEAD - 1) asm volatile("bar.arrive %0, 256;" ::"r"(wgu == 2 ? 8 : 9 + wgu) : "memory");
                }
            }
            asm volatile("wgmma.commit_group.sync.aligned;" ::: "memory");
        }
        asm volatile("wgmma.wait_group.sync.aligned 0;" ::: "memory");
#pragma unroll
        for (int j = 0; j < 16; j++) asm volatile("" : "+f"(d[j])::"memory");
        if (lane == 0) mbar_arrive_cluster(bar_empty + lead);

        uint32_t st_base = smem + SMEM_OUT + wg * 1024 + (lane >> 4) * 3072 + (lane & 7) * 128 + swz;
        asm volatile("" : "+r"(st_base), "+r"(bias2));

        int s = 1, ob = 0, i = 1;
        uint32_t ph = 0, oph = 1;
        uint32_t q[KREG][8];
        auto compute = [&]() -> bool {
            mbar_wait(bar_full + 8 * s, ph);
            if (lds(tile_slot + 4 * (i & 31)) < 0) return false;
            const uint64_t desc = desc0 + (uint64_t)(s * (STAGE_BYTES >> 4));
            asm volatile("bar.sync %0, 256;" ::"r"(8 + wgu) : "memory");
            asm volatile("wgmma.fence.sync.aligned;" ::: "memory");
#pragma unroll
            for (int ks = 0; ks < 24; ks++) {
                wgmma_rs(d, a[ks], desc + (uint64_t)(((ks >> 2) * 1024 + (ks & 3) * 32) >> 4), ks != 0);
                if (ks == HANDOVER - 1) asm volatile("bar.arrive %0, 256;" ::"r"(wgu == 2 ? 8 : 9 + wgu) : "memory");
            }
            asm volatile("wgmma.commit_group.sync.aligned;" ::: "memory");
            asm volatile("wgmma.wait_group.sync.aligned 0;" ::: "memory");
#pragma unroll
            for (int j = 0; j < 16; j++) asm volatile("" : "+f"(d[j])::"memory");
            if (lane == 0) mbar_arrive_cluster(bar_empty + 8 * s + lead);
            if (++s == STAGES) { s = 0; ph ^= 1; }
            return true;
        };
        auto pack = [&](uint32_t (&p)[8]) {
#pragma unroll
            for (int j = 0; j < 8; j += 2) {
                p[j]     = cvt_add_bias<false>(d[2 * j], d[2 * j + 1], bias2);
                p[j + 1] = cvt_add_bias<true>(d[2 * j + 2], d[2 * j + 3], bias2);
            }
        };
        auto put = [&](uint32_t st, const uint32_t (&p)[8]) {
#pragma unroll
            for (int j = 0; j < 2; j++)
                asm volatile("stmatrix.sync.aligned.m8n8.x4.trans.shared.b16 [%0], {%1,%2,%3,%4};"
                             ::"r"(st + j * 6144), "r"(p[4 * j]), "r"(p[4 * j + 1]), "r"(p[4 * j + 2]), "r"(p[4 * j + 3])
                             : "memory");
        };
        auto acquire = [&]() -> uint32_t {
            mbar_wait(bar_oempty + 8 * ob, oph);
            return st_base + ob * OUT_BYTES;
        };
        auto publish = [&]() {
            fence_async_smem();
            __syncwarp();
            if (lane == 0) mbar_arrive(bar_ofull + 8 * ob);
            if (++ob == NBUF) { ob = 0; oph ^= 1; }
        };

        const int kstart = KSTART - cluster_id % KRAMP;
        int held = 0, h = 0;
        bool more = true;
        pack(q[0]);
        mbar_wait(bar_wloc, 0);
        put(acquire(), q[0]);
        publish();
#pragma unroll 1
        for (; i < kstart; i++) {
            more = compute();
            if (!more) break;
            pack(q[0]);
            put(acquire(), q[0]);
            publish();
        }
        if (more) {
            int kstep = kstart;
#pragma unroll 1
            for (; compute(); i++) {
                if (h == 0 && i >= kstep) {
#pragma unroll
                    for (int k = 0; k < KREG; k++)
                        if (held == k) pack(q[k]);
                    kstep = ++held == KREG ? 0x7fffffff : kstep + KRAMP;
                    continue;
                }
                const uint32_t st = acquire();
#pragma unroll
                for (int k = 0; k < KREG; k++)
                    if (h == k) { put(st, q[k]); pack(q[k]); }
                publish();
                if (++h == held) h = 0;
            }
#pragma unroll 1
            for (int left = held; left > 0; left--) {
                const uint32_t st = acquire();
#pragma unroll
                for (int k = 0; k < KREG; k++)
                    if (h == k) put(st, q[k]);
                publish();
                if (++h == held) h = 0;
            }
        }
        if (wg == 0) asm volatile("bar.sync 8, 256;" ::: "memory");
    }
}

typedef CUresult (*EncodeTiledFn)(CUtensorMap*, CUtensorMapDataType, cuuint32_t, void*, const cuuint64_t*,
                                  const cuuint64_t*, const cuuint32_t*, const cuuint32_t*, CUtensorMapInterleave,
                                  CUtensorMapSwizzle, CUtensorMapL2promotion, CUtensorMapFloatOOBfill);

void encode_map(EncodeTiledFn fn, CUtensorMap* tm, const void* ptr, int rank, const cuuint64_t* dims,
                const cuuint64_t* strides, const cuuint32_t* box) {
    const cuuint32_t estr[4] = {1, 1, 1, 1};
    fn(tm, CU_TENSOR_MAP_DATA_TYPE_BFLOAT16, rank, const_cast<void*>(ptr), dims, strides, box, estr,
       CU_TENSOR_MAP_INTERLEAVE_NONE, CU_TENSOR_MAP_SWIZZLE_128B, CU_TENSOR_MAP_L2_PROMOTION_L2_128B,
       CU_TENSOR_MAP_FLOAT_OOB_FILL_NONE);
}

}

extern "C" void kernel_launch(void* const* d_in, const int* in_sizes, int n_in, void* d_out, int out_size) {
    const __nv_bfloat16* x = (const __nv_bfloat16*)d_in[0];
    const __nv_bfloat16* w = (const __nv_bfloat16*)d_in[1];
    const __nv_bfloat16* b = (const __nv_bfloat16*)d_in[2];
    const int pixels = in_sizes[0] / C;

    static EncodeTiledFn encode = nullptr;
    static int max_clusters = 0;
    if (!encode) {
        void* fn = nullptr;
        cudaDriverEntryPointQueryResult qr;
        cudaGetDriverEntryPoint("cuTensorMapEncodeTiled", &fn, cudaEnableDefault, &qr);
        encode = (EncodeTiledFn)fn;
        cudaFuncSetAttribute(conv1x1_kernel, cudaFuncAttributeMaxDynamicSharedMemorySize, SMEM_TOTAL);
        cudaLaunchConfig_t cfg = {};
        cfg.gridDim = dim3(2, 1, 1);
        cfg.blockDim = dim3(NTHREADS, 1, 1);
        cfg.dynamicSmemBytes = SMEM_TOTAL;
        cudaLaunchAttribute at[1];
        at[0].id = cudaLaunchAttributeClusterDimension;
        at[0].val.clusterDim.x = 2; at[0].val.clusterDim.y = 1; at[0].val.clusterDim.z = 1;
        cfg.attrs = at; cfg.numAttrs = 1;
        if (cudaOccupancyMaxActiveClusters(&max_clusters, conv1x1_kernel, &cfg) != cudaSuccess || max_clusters <= 0) {
            (void)cudaGetLastError();
            int dev = 0, sms = 0;
            cudaGetDevice(&dev);
            cudaDeviceGetAttribute(&sms, cudaDevAttrMultiProcessorCount, dev);
            max_clusters = sms / 2;
        }
    }
    CUtensorMap tm_x, tm_w, tm_o, tm_p;
    {
        const cuuint64_t dims[4]    = {64, 8, 6, (cuuint64_t)(pixels / 8)};
        const cuuint64_t strides[3] = {C * 2, 128, C * 2 * 8};
        const cuuint32_t box_x[4]   = {64, 8, 6, TP / 8};
        const cuuint32_t box_o[4]   = {64, 8, 3, TP / 8};
        encode_map(encode, &tm_x, x, 4, dims, strides, box_x);
        encode_map(encode, &tm_o, d_out, 4, dims, strides, box_o);
        const cuuint64_t pdims[2]    = {64, (cuuint64_t)pixels * 6};
        const cuuint64_t pstrides[1] = {128};
        const cuuint32_t pbox[2]     = {64, STAGE_BYTES / 128};
        encode_map(encode, &tm_p, x, 2, pdims, pstrides, pbox);
        const cuuint64_t wdims[3]    = {64, C, 6};
        const cuuint64_t wstrides[2] = {C * 2, 128};
        const cuuint32_t wbox[3]     = {64, 64, 3};
        encode_map(encode, &tm_w, w, 3, wdims, wstrides, wbox);
    }
    const int num_units = pixels / (TP * UNIT);
    const int nclusters = max_clusters * NSTATIC <= num_units ? max_clusters : num_units / NSTATIC;
    conv1x1_kernel<<<2 * nclusters, NTHREADS, SMEM_TOTAL, cudaStreamPerThread>>>(x, w, b, num_units, tm_x, tm_w, tm_o, tm_p);
}
```
